```python
import torch

def _softmax(x, axis=-1):
    return torch.softmax(x, dim=axis)
def _gelu(x):
    return torch.nn.functional.gelu(x, approximate="tanh")
def _silu(x):
    return torch.nn.functional.silu(x)
def _sigmoid(x):
    return torch.sigmoid(x)
def _layernorm(x, axis=-1, eps=1e-5):
    m = x.mean(dim=axis, keepdim=True)
    v = x.var(dim=axis, keepdim=True, unbiased=False)
    return (x - m) / torch.sqrt(v + eps)
def _scatter_add(tgt, idx, src, axis=0):
    return tgt.clone().index_add_(axis, idx, src)
def _segment_sum(src, seg, n):
    out = torch.zeros((n,) + src.shape[1:], dtype=src.dtype)
    return out.index_add_(0, seg, src)
def _pad(x, pw):
    flat = tuple(v for pair in reversed(pw) for v in pair)
    return torch.nn.functional.pad(x, flat)

kernel_name = 'recurrent_scan__mha_block_cached__moe_arch_mod__prompt'

def setup_inputs():

    _w = (lambda a: (lambda t: t.to(torch.bfloat16) if t.is_floating_point() else t)(torch.as_tensor(a)))
    def _A_setup():
        B, Sq, D = 1, 2048, 640
        H, Sk, Dh = 32, 2048, 128
        return {
            "x": _w((lambda *s: torch.randn(*s, dtype=torch.bfloat16) * 0.05)(B, Sq, D)),
            "k_cache": _w((lambda *s: torch.randn(*s, dtype=torch.bfloat16) * 1.6)(B, H, Sk, Dh)),
            "v_cache": _w((lambda *s: torch.randn(*s, dtype=torch.bfloat16) * 0.2)(B, H, Sk, Dh)),
            "wq": _w((lambda *s: torch.randn(*s, dtype=torch.bfloat16) * 1.6)(D, H * Dh) * (D ** -0.5)),
            "wo": _w((lambda *s: torch.randn(*s, dtype=torch.bfloat16) * 0.2)(H * Dh, D) * ((H * Dh) ** -0.5)),
        }
    _A_in = _A_setup()

    def _B_setup():
        B, S, D, F, C = 1, 2048, 640, 1728, 8
        return {
            "x": _w((lambda *s: torch.randn(*s, dtype=torch.bfloat16) * 0.05)(B, S, D)),
            "w_r": _w((lambda *s: torch.randn(*s, dtype=torch.bfloat16) * 0.2)(D)),
            "w_gate": _w((lambda *s: torch.randn(*s, dtype=torch.bfloat16) * 0.1)(D, F)),
            "w_up": _w((lambda *s: torch.randn(*s, dtype=torch.bfloat16) * 0.1)(D, F)),
            "w_down": _w((lambda *s: torch.randn(*s, dtype=torch.bfloat16) * 0.1)(F, D)),
        }
    _B_in = _B_setup()

    return {
        "A_x": _A_in["x"],
        "A_k_cache": _A_in["k_cache"],
        "A_v_cache": _A_in["v_cache"],
        "A_wq": _A_in["wq"],
        "A_wo": _A_in["wo"],
        "B_x": _B_in["x"],
        "B_w_r": _B_in["w_r"],
        "B_w_gate": _B_in["w_gate"],
        "B_w_up": _B_in["w_up"],
        "B_w_down": _B_in["w_down"],
    }

def reference(A_x, A_k_cache, A_v_cache, A_wq, A_wo, B_x, B_w_r, B_w_gate, B_w_up, B_w_down):
    def _A_ref(x, k_cache, v_cache, wq, wo):
        B, Sq, D = x.shape
        H, Dh = 32, 128
        q = (lambda x, *d: x.permute(*d))((x @ wq).reshape(B, Sq, H, Dh), 0, 2, 1, 3)
        scores = torch.einsum("bhqd,bhkd->bhqk", q, k_cache) * (Dh ** -0.5)
        p = _softmax(scores, axis=-1)
        o = torch.einsum("bhqk,bhkd->bhqd", p, v_cache)
        return (lambda x, *d: x.permute(*d))(o, 0, 2, 1, 3).reshape(B, Sq, H * Dh) @ wo

    def _B_ref(x, w_r, w_gate, w_up, w_down):
        B, S, D = x.shape
        C = 8
        r = x @ w_r
        idx = torch.argsort(-r, axis=-1)[:, :C]
        idx_e = (lambda x, n, axis: torch.repeat_interleave(x, n, dim=axis))(idx.reshape(B, C, 1), D, axis=2)
        x_sel = (lambda x, i, axis: torch.take_along_dim(x, i, dim=axis))(x, idx_e, axis=1)
        g = _silu(x_sel @ w_gate)
        u = x_sel @ w_up
        y = (g * u) @ w_down
        r_sel = _sigmoid((lambda x, i, axis: torch.take_along_dim(x, i, dim=axis))(r, idx, axis=1))
        y = y * r_sel.reshape(B, C, 1)
        b_off = (torch.arange(B) * S).reshape(B, 1)
        flat_idx = (idx + b_off).reshape(B * C)
        zero = (x * 0.0).reshape(B * S, D)
        upd = _scatter_add(zero, flat_idx, y.reshape(B * C, D), axis=0)
        return x + upd.reshape(B, S, D)

    x = A_x
    xn = _layernorm(x, axis=-1)
    s = _A_ref(xn, A_k_cache, A_v_cache, A_wq, A_wo)
    g = _silu(_B_ref(xn, B_w_r, B_w_gate, B_w_up, B_w_down))
    return x + s * g
```

```cpp
#include <cuda_runtime.h>
#include <cuda.h>
#include <cuda_bf16.h>
#include <stdint.h>

namespace {

constexpr int SEQ = 2048, DM = 640, NH = 32, DH = 128, FF = 1728, CAP = 8;
constexpr int NSLOT = 4;
constexpr int TILE_BYTES = 32768;
constexpr uint32_t RING_OFFSET = 1024;
constexpr int SMEM_BYTES = (NSLOT + 3) * TILE_BYTES + 400 + 1408 + 96;
constexpr int N_MAIN = 128, N_MOE = 4;

struct Scratch {
    uint4 part[16 * 8 * 9 * 2 * 4 * 128];
    uint4 gate[N_MAIN * 5 * 2 * 256];
    uint4 flag[16 * 8 * 32];
    uint4 qoff[16 * 4 * 2048];
    uint32_t flag_q[16];
    uint4 rare[N_MAIN * 16 * 256];
    float y[N_MOE * CAP * DM];
    uint2 routed[CAP * DM / 4];
    uint2 stat[SEQ];
    float r[SEQ];
    int idx[CAP];
    uint32_t flag_r[N_MOE], flag_y[N_MOE], flag_u[N_MOE];
    uint32_t epoch[N_MAIN + N_MOE];
};
__device__ Scratch g_scratch;

__device__ __forceinline__ uint32_t smem_u32(const void* p) { return (uint32_t)__cvta_generic_to_shared(p); }
__device__ __forceinline__ void mbar_init(uint32_t bar, uint32_t cnt) {
    asm volatile("mbarrier.init.shared::cta.b64 [%0], %1;" ::"r"(bar), "r"(cnt) : "memory");
}
__device__ __forceinline__ void mbar_wait(uint32_t bar, uint32_t parity) {
    asm volatile(
        "{\n.reg .pred p;\n.reg .u32 c;\n"
        "mbarrier.test_wait.parity.shared::cta.b64 p, [%0], %1;\n"
        "@p bra.uni DONE;\n"
        "mov.u32 c, 0;\n"
        "LOOP:\n"
        "mbarrier.try_wait.parity.shared::cta.b64 p, [%0], %1;\n"
        "@p bra.uni DONE;\n"
        "add.u32 c, c, 1;\n"
        "setp.lt.u32 p, c, 2000000;\n"
        "@p bra.uni LOOP;\n"
        "trap;\n"
        "DONE:\n}\n" ::"r"(bar), "r"(parity) : "memory");
}
__device__ __forceinline__ void mbar_wait_sleep(uint32_t bar, uint32_t parity) {
    asm volatile(
        "{\n.reg .pred p;\n.reg .u32 c;\n"
        "mov.u32 c, 0;\n"
        "LOOP:\n"
        "mbarrier.test_wait.parity.shared::cta.b64 p, [%0], %1;\n"
        "@p bra.uni DONE;\n"
        "nanosleep.u32 500;\n"
        "add.u32 c, c, 1;\n"
        "setp.lt.u32 p, c, 1000000;\n"
        "@p bra.uni LOOP;\n"
        "trap;\n"
        "DONE:\n}\n" ::"r"(bar), "r"(parity) : "memory");
}
__device__ __forceinline__ void mbar_expect_tx(uint32_t bar, uint32_t bytes) {
    asm volatile("mbarrier.arrive.expect_tx.shared::cta.b64 _, [%0], %1;" ::"r"(bar), "r"(bytes) : "memory");
}
template <int OFF>
__device__ __forceinline__ void release_at(uint32_t bar) {
    asm volatile(
        "{\n.reg .pred p;\n"
        "setp.ne.u32 p, %0, 0;\n"
        "@p mbarrier.arrive.shared::cluster.b64 _, [%0 + %1];\n}\n" ::"r"(bar), "n"(OFF) : "memory");
}
__device__ __forceinline__ void sched_fence(int zero) {
    asm volatile("{\n.reg .pred p;\n.reg .u32 c;\nsetp.ne.s32 p, %0, 0;\n@p mov.u32 c, %%clock;\n@p st.shared.u32 [%0], c;\n}\n" ::"r"(zero) : "memory");
}
__device__ __forceinline__ bool elect_one() {
    uint32_t r;
    asm volatile("{\n.reg .pred p;\nelect.sync _|p, 0xffffffff;\nselp.u32 %0, 1, 0, p;\n}\n" : "=r"(r));
    return r;
}
__device__ __forceinline__ uint32_t opaque(uint32_t v) {
    uint32_t r;
    asm volatile("mov.u32 %0, %1;" : "=r"(r) : "r"(v));
    return r;
}
__device__ __forceinline__ void tma_2d(uint32_t dst, const CUtensorMap* tm, uint32_t bar, int c0, int c1) {
    asm volatile(
        "cp.async.bulk.tensor.2d.shared::cluster.global.mbarrier::complete_tx::bytes [%0], [%1, {%3, %4}], [%2];"
        ::"r"(dst), "l"(tm), "r"(bar), "r"(c0), "r"(c1) : "memory");
}
__device__ __forceinline__ void tma_3d(uint32_t dst, const CUtensorMap* tm, uint32_t bar, int c0, int c1, int c2) {
    asm volatile(
        "cp.async.bulk.tensor.3d.shared::cluster.global.mbarrier::complete_tx::bytes [%0], [%1, {%3, %4, %5}], [%2];"
        ::"r"(dst), "l"(tm), "r"(bar), "r"(c0), "r"(c1), "r"(c2) : "memory");
}
__device__ __forceinline__ void tma_2d_mc(uint32_t dst, const CUtensorMap* tm, uint32_t bar, int c0, int c1) {
    asm volatile(
        "cp.async.bulk.tensor.2d.shared::cluster.global.mbarrier::complete_tx::bytes.multicast::cluster "
        "[%0], [%1, {%3, %4}], [%2], %5;"
        ::"r"(dst), "l"(tm), "r"(bar), "r"(c0), "r"(c1), "h"((uint16_t)3) : "memory");
}
__device__ __forceinline__ void tma_prefetch(const CUtensorMap* tm, int c0, int c1) {
    asm volatile("cp.async.bulk.prefetch.tensor.2d.L2.global [%0, {%1, %2}];" ::"l"(tm), "r"(c0), "r"(c1) : "memory");
}
__device__ __forceinline__ void mbar_arrive(uint32_t bar) {
    asm volatile("mbarrier.arrive.shared::cta.b64 _, [%0];" ::"r"(bar) : "memory");
}
__device__ __forceinline__ void flag_set(uint32_t* f, uint32_t v) {
    asm volatile("st.release.gpu.global.u32 [%0], %1;" ::"l"(f), "r"(v) : "memory");
}
template <int SLEEP_NS = 0>
__device__ __forceinline__ void flag_wait(const uint32_t* f, uint32_t v) {
    asm volatile(
        "{\n.reg .pred p;\n.reg .u32 c, n;\n"
        "mov.u32 n, 0;\n"
        "LOOP:\n"
        "setp.ne.u32 p, %2, 0;\n"
        "@p nanosleep.u32 %2;\n"
        "ld.acquire.gpu.global.u32 c, [%0];\n"
        "setp.eq.u32 p, c, %1;\n"
        "@p bra DONE;\n"
        "add.u32 n, n, 1;\n"
        "setp.lt.u32 p, n, %3;\n"
        "@p bra LOOP;\n"
        "trap;\n"
        "DONE:\n}\n" ::"l"(f), "r"(v), "n"(SLEEP_NS), "n"(SLEEP_NS ? 500000 : 4000000) : "memory");
}
__device__ __forceinline__ void hmma(float (&d)[4], uint32_t a0, uint32_t a1, uint32_t a2, uint32_t a3, uint32_t b0, uint32_t b1) {
    asm volatile("mma.sync.aligned.m16n8k16.row.col.f32.bf16.bf16.f32 {%0,%1,%2,%3}, {%4,%5,%6,%7}, {%8,%9}, {%0,%1,%2,%3};"
                 : "+f"(d[0]), "+f"(d[1]), "+f"(d[2]), "+f"(d[3]) : "r"(a0), "r"(a1), "r"(a2), "r"(a3), "r"(b0), "r"(b1));
}
__device__ __forceinline__ void hmma8(float (&d)[4], uint32_t a0, uint32_t a1, uint32_t b0) {
    asm volatile("mma.sync.aligned.m16n8k8.row.col.f32.bf16.bf16.f32 {%0,%1,%2,%3}, {%4,%5}, {%6}, {%0,%1,%2,%3};"
                 : "+f"(d[0]), "+f"(d[1]), "+f"(d[2]), "+f"(d[3]) : "r"(a0), "r"(a1), "r"(b0));
}
__device__ __forceinline__ void ldsm4(uint32_t addr, uint32_t& a, uint32_t& b, uint32_t& c, uint32_t& d) {
    asm volatile("ldmatrix.sync.aligned.m8n8.x4.shared.b16 {%0, %1, %2, %3}, [%4];"
                 : "=r"(a), "=r"(b), "=r"(c), "=r"(d) : "r"(addr) : "memory");
}
__device__ __forceinline__ void stsm4(uint32_t addr, uint32_t a, uint32_t b, uint32_t c, uint32_t d) {
    asm volatile("stmatrix.sync.aligned.m8n8.x4.shared.b16 [%4], {%0, %1, %2, %3};"
                 ::"r"(a), "r"(b), "r"(c), "r"(d), "r"(addr) : "memory");
}
__device__ __forceinline__ uint32_t bf2_sub(uint32_t a, uint32_t b) {
    uint32_t d;
    asm("sub.rn.bf16x2 %0, %1, %2;" : "=r"(d) : "r"(a), "r"(b));
    return d;
}
template <int LUT>
__device__ __forceinline__ uint32_t lop3(uint32_t a, uint32_t b, uint32_t c) {
    uint32_t d;
    asm("lop3.b32 %0, %1, %2, %3, %4;" : "=r"(d) : "r"(a), "r"(b), "r"(c), "n"(LUT));
    return d;
}
__device__ __forceinline__ float rcp(float x) {
    float y;
    asm("rcp.approx.ftz.f32 %0, %1;" : "=f"(y) : "f"(x));
    return y;
}
__device__ __forceinline__ void bar_sync(int id) { asm volatile("bar.sync %0, 256;" ::"r"(id) : "memory"); }
__device__ __forceinline__ void bar_arrive(int id) { asm volatile("bar.arrive %0, 256;" ::"r"(id) : "memory"); }
__device__ __forceinline__ void wg_fence() { asm volatile("wgmma.fence.sync.aligned;" ::: "memory"); }
__device__ __forceinline__ void wg_commit() { asm volatile("wgmma.commit_group.sync.aligned;" ::: "memory"); }
template <int N> __device__ __forceinline__ void wg_wait() { asm volatile("wgmma.wait_group.sync.aligned %0;" ::"n"(N) : "memory"); }
template <int N>
__device__ __forceinline__ void pin(float (&d)[N]) {
#pragma unroll
    for (int i = 0; i < N; i++) asm volatile("" : "+f"(d[i])::"memory");
}
__device__ __forceinline__ uint32_t pack_bf16(float lo, float hi) {
    uint32_t r;
    asm("cvt.rn.bf16x2.f32 %0, %1, %2;" : "=r"(r) : "f"(hi), "f"(lo));
    return r;
}
__device__ __forceinline__ float bf_lo(uint32_t v) { return __uint_as_float(v << 16); }
__device__ __forceinline__ float bf_hi(uint32_t v) { return __uint_as_float(v & 0xffff0000u); }
__device__ __forceinline__ float bf_round(float v) { return __bfloat162float(__float2bfloat16_rn(v)); }
__device__ __forceinline__ float ex2(float x) {
    float y;
    asm("ex2.approx.ftz.f32 %0, %1;" : "=f"(y) : "f"(x));
    return y;
}
__device__ __forceinline__ void sts128(uint32_t addr, uint32_t a, uint32_t b, uint32_t c, uint32_t d) {
    asm volatile("st.shared.v4.b32 [%0], {%1, %2, %3, %4};" ::"r"(addr), "r"(a), "r"(b), "r"(c), "r"(d) : "memory");
}
__device__ __forceinline__ void lds128(uint32_t addr, uint32_t& a, uint32_t& b, uint32_t& c, uint32_t& d) {
    asm volatile("ld.shared.v4.b32 {%0, %1, %2, %3}, [%4];" : "=r"(a), "=r"(b), "=r"(c), "=r"(d) : "r"(addr) : "memory");
}

template <int OFF>
__device__ __forceinline__ void lds128_if(bool on, uint32_t addr, uint32_t& a, uint32_t& b, uint32_t& c, uint32_t& d) {
    asm volatile("{\n.reg .pred p;\nsetp.ne.u32 p, %5, 0;\n@p ld.shared.v4.b32 {%0, %1, %2, %3}, [%4 + %6];\n}\n"
                 : "+r"(a), "+r"(b), "+r"(c), "+r"(d) : "r"(addr), "r"((uint32_t)on), "n"(OFF) : "memory");
}

template <int TB>
__device__ __forceinline__ void wgmma_rs(float (&d)[64], uint32_t a0, uint32_t a1, uint32_t a2, uint32_t a3,
                                         uint64_t desc, int scale_d) {
    asm volatile(
        "{\n.reg .pred p;\nsetp.ne.b32 p, %69, 0;\n"
        "wgmma.mma_async.sync.aligned.m64n128k16.f32.bf16.bf16 "
        "{%0,%1,%2,%3,%4,%5,%6,%7,%8,%9,%10,%11,%12,%13,%14,%15,%16,%17,%18,%19,%20,%21,%22,%23,%24,%25,%26,%27,%28,%29,%30,%31,"
        "%32,%33,%34,%35,%36,%37,%38,%39,%40,%41,%42,%43,%44,%45,%46,%47,%48,%49,%50,%51,%52,%53,%54,%55,%56,%57,%58,%59,%60,%61,%62,%63},"
        "{%64,%65,%66,%67}, %68, p, 1, 1, %70;\n}\n"
        : "+f"(d[0]), "+f"(d[1]), "+f"(d[2]), "+f"(d[3]), "+f"(d[4]), "+f"(d[5]), "+f"(d[6]), "+f"(d[7]),
          "+f"(d[8]), "+f"(d[9]), "+f"(d[10]), "+f"(d[11]), "+f"(d[12]), "+f"(d[13]), "+f"(d[14]), "+f"(d[15]),
          "+f"(d[16]), "+f"(d[17]), "+f"(d[18]), "+f"(d[19]), "+f"(d[20]), "+f"(d[21]), "+f"(d[22]), "+f"(d[23]),
          "+f"(d[24]), "+f"(d[25]), "+f"(d[26]), "+f"(d[27]), "+f"(d[28]), "+f"(d[29]), "+f"(d[30]), "+f"(d[31]),
          "+f"(d[32]), "+f"(d[33]), "+f"(d[34]), "+f"(d[35]), "+f"(d[36]), "+f"(d[37]), "+f"(d[38]), "+f"(d[39]),
          "+f"(d[40]), "+f"(d[41]), "+f"(d[42]), "+f"(d[43]), "+f"(d[44]), "+f"(d[45]), "+f"(d[46]), "+f"(d[47]),
          "+f"(d[48]), "+f"(d[49]), "+f"(d[50]), "+f"(d[51]), "+f"(d[52]), "+f"(d[53]), "+f"(d[54]), "+f"(d[55]),
          "+f"(d[56]), "+f"(d[57]), "+f"(d[58]), "+f"(d[59]), "+f"(d[60]), "+f"(d[61]), "+f"(d[62]), "+f"(d[63])
        : "r"(a0), "r"(a1), "r"(a2), "r"(a3), "l"(desc), "r"(scale_d), "n"(TB));
}
__device__ __forceinline__ void wgmma_ss(float (&d)[64], uint64_t desc_a, uint64_t desc_b, int scale_d) {
    asm volatile(
        "{\n.reg .pred p;\nsetp.ne.b32 p, %66, 0;\n"
        "wgmma.mma_async.sync.aligned.m64n128k16.f32.bf16.bf16 "
        "{%0,%1,%2,%3,%4,%5,%6,%7,%8,%9,%10,%11,%12,%13,%14,%15,%16,%17,%18,%19,%20,%21,%22,%23,%24,%25,%26,%27,%28,%29,%30,%31,"
        "%32,%33,%34,%35,%36,%37,%38,%39,%40,%41,%42,%43,%44,%45,%46,%47,%48,%49,%50,%51,%52,%53,%54,%55,%56,%57,%58,%59,%60,%61,%62,%63},"
        "%64, %65, p, 1, 1, 0, 1;\n}\n"
        : "+f"(d[0]), "+f"(d[1]), "+f"(d[2]), "+f"(d[3]), "+f"(d[4]), "+f"(d[5]), "+f"(d[6]), "+f"(d[7]),
          "+f"(d[8]), "+f"(d[9]), "+f"(d[10]), "+f"(d[11]), "+f"(d[12]), "+f"(d[13]), "+f"(d[14]), "+f"(d[15]),
          "+f"(d[16]), "+f"(d[17]), "+f"(d[18]), "+f"(d[19]), "+f"(d[20]), "+f"(d[21]), "+f"(d[22]), "+f"(d[23]),
          "+f"(d[24]), "+f"(d[25]), "+f"(d[26]), "+f"(d[27]), "+f"(d[28]), "+f"(d[29]), "+f"(d[30]), "+f"(d[31]),
          "+f"(d[32]), "+f"(d[33]), "+f"(d[34]), "+f"(d[35]), "+f"(d[36]), "+f"(d[37]), "+f"(d[38]), "+f"(d[39]),
          "+f"(d[40]), "+f"(d[41]), "+f"(d[42]), "+f"(d[43]), "+f"(d[44]), "+f"(d[45]), "+f"(d[46]), "+f"(d[47]),
          "+f"(d[48]), "+f"(d[49]), "+f"(d[50]), "+f"(d[51]), "+f"(d[52]), "+f"(d[53]), "+f"(d[54]), "+f"(d[55]),
          "+f"(d[56]), "+f"(d[57]), "+f"(d[58]), "+f"(d[59]), "+f"(d[60]), "+f"(d[61]), "+f"(d[62]), "+f"(d[63])
        : "l"(desc_a), "l"(desc_b), "r"(scale_d));
}
__device__ __forceinline__ void wgmma_rs64(float (&d)[32], uint32_t a0, uint32_t a1, uint32_t a2, uint32_t a3,
                                           uint64_t desc, int scale_d) {
    asm volatile(
        "{\n.reg .pred p;\nsetp.ne.b32 p, %37, 0;\n"
        "wgmma.mma_async.sync.aligned.m64n64k16.f32.bf16.bf16 "
        "{%0,%1,%2,%3,%4,%5,%6,%7,%8,%9,%10,%11,%12,%13,%14,%15,%16,%17,%18,%19,%20,%21,%22,%23,%24,%25,%26,%27,%28,%29,%30,%31},"
        "{%32,%33,%34,%35}, %36, p, 1, 1, 1;\n}\n"
        : "+f"(d[0]), "+f"(d[1]), "+f"(d[2]), "+f"(d[3]), "+f"(d[4]), "+f"(d[5]), "+f"(d[6]), "+f"(d[7]),
          "+f"(d[8]), "+f"(d[9]), "+f"(d[10]), "+f"(d[11]), "+f"(d[12]), "+f"(d[13]), "+f"(d[14]), "+f"(d[15]),
          "+f"(d[16]), "+f"(d[17]), "+f"(d[18]), "+f"(d[19]), "+f"(d[20]), "+f"(d[21]), "+f"(d[22]), "+f"(d[23]),
          "+f"(d[24]), "+f"(d[25]), "+f"(d[26]), "+f"(d[27]), "+f"(d[28]), "+f"(d[29]), "+f"(d[30]), "+f"(d[31])
        : "r"(a0), "r"(a1), "r"(a2), "r"(a3), "l"(desc), "r"(scale_d));
}
__device__ __forceinline__ void wgmma_ss64(float (&d)[32], uint64_t desc_a, uint64_t desc_b, int scale_d) {
    asm volatile(
        "{\n.reg .pred p;\nsetp.ne.b32 p, %34, 0;\n"
        "wgmma.mma_async.sync.aligned.m64n64k16.f32.bf16.bf16 "
        "{%0,%1,%2,%3,%4,%5,%6,%7,%8,%9,%10,%11,%12,%13,%14,%15,%16,%17,%18,%19,%20,%21,%22,%23,%24,%25,%26,%27,%28,%29,%30,%31},"
        "%32, %33, p, 1, 1, 0, 1;\n}\n"
        : "+f"(d[0]), "+f"(d[1]), "+f"(d[2]), "+f"(d[3]), "+f"(d[4]), "+f"(d[5]), "+f"(d[6]), "+f"(d[7]),
          "+f"(d[8]), "+f"(d[9]), "+f"(d[10]), "+f"(d[11]), "+f"(d[12]), "+f"(d[13]), "+f"(d[14]), "+f"(d[15]),
          "+f"(d[16]), "+f"(d[17]), "+f"(d[18]), "+f"(d[19]), "+f"(d[20]), "+f"(d[21]), "+f"(d[22]), "+f"(d[23]),
          "+f"(d[24]), "+f"(d[25]), "+f"(d[26]), "+f"(d[27]), "+f"(d[28]), "+f"(d[29]), "+f"(d[30]), "+f"(d[31])
        : "l"(desc_a), "l"(desc_b), "r"(scale_d));
}
__device__ __forceinline__ uint64_t desc_kmajor(uint32_t tile16, int ks) {
    uint32_t lo = tile16 + ((ks >> 2) * 1024 + (ks & 3) * 2 + (1u << 16));
    return ((uint64_t)0x40000040u << 32) | lo;
}
__device__ __forceinline__ uint64_t desc_nmajor(uint32_t tile16, int ks) {
    uint32_t lo = tile16 + (ks * 128 + (1024u << 16));
    return ((uint64_t)0x40000040u << 32) | lo;
}
template <int TB>
__device__ __forceinline__ void mma_tile(float (&d)[64], const uint32_t* a, uint32_t tile16, int accumulate) {
#pragma unroll
    for (int ks = 0; ks < 8; ks++)
        wgmma_rs<TB>(d, a[4 * ks], a[4 * ks + 1], a[4 * ks + 2], a[4 * ks + 3],
                     TB ? desc_nmajor(tile16, ks) : desc_kmajor(tile16, ks), ks == 0 ? accumulate : 1);
    wg_commit();
}

#define RARE(x) (x)
template <int V> struct cint { static constexpr int value = V; };
#define GPF 126
#define XN 2
#define QAT 110
#define FSPLIT 4
#define SPLIT 16

#define TR(i)
#define TG(i)
#define PT(k)
#define TS(k)
#define TA(k)
#define TL(k)
#define TF(i)
#define TH(w, i)
#define TC(k)

__device__ __forceinline__ float silu_f(float v) { return v * rcp(1.f + ex2(v * -1.4426950408889634f)); }

__device__ __forceinline__ float inv_den(float var) {
    float r;
    asm("sqrt.approx.f32 %0, %1;" : "=f"(r) : "f"(bf_round(bf_round(var) + 1e-5f)));
    return rcp(bf_round(r));
}
__device__ __forceinline__ uint32_t normalise(uint32_t x2, uint32_t mm, float id) {
    const uint32_t d = bf2_sub(x2, mm);
    return pack_bf16(bf_lo(d) * id, bf_hi(d) * id);
}

__device__ __forceinline__ uint32_t silu2(uint32_t u) { return pack_bf16(silu_f(bf_lo(u)), silu_f(bf_hi(u))); }

__device__ __forceinline__ uint32_t silu2_ln(uint32_t u) {
    const float a = bf_lo(u), b = bf_hi(u);
    const float da = 1.f + ex2(a * -1.4426950408889634f), db = 1.f + ex2(b * -1.4426950408889634f);
    const float r = rcp(da * db);
    return pack_bf16(a * db * r, b * da * r);
}

__device__ __forceinline__ uint2 load_stat(Scratch* sc, int row) {
    uint2 v;
    asm volatile("ld.relaxed.gpu.global.v2.u32 {%0, %1}, [%2];" : "=r"(v.x), "=r"(v.y) : "l"(sc->stat + row) : "memory");
    return make_uint2(__byte_perm(v.x, 0, 0x1010), v.y);
}

constexpr int FSLOT = 6;
__device__ __forceinline__ void ffn_role(Scratch* sc, uint32_t ring, uint32_t ffull, uint32_t fempty, int e, uint32_t ep, int warp,
                                         const __nv_bfloat16* __restrict__ x) {
    const uint32_t xs = ring + FSLOT * TILE_BYTES, hs = xs + 10 * 1024, cand = hs + 8 * 1024, sig = cand + 256;
    int tid;
    asm volatile("mov.u32 %0, %%tid.x;" : "=r"(tid));
    const int lane = tid & 31;
    [[maybe_unused]] const int wg = warp >> 2;
    const int nb = e == N_MOE - 1 ? 6 : 7, nkt = (nb + 1) >> 1;
    auto sync = [] { asm volatile("bar.sync 3, 256;" ::: "memory"); };
    if (tid < N_MOE) flag_wait(sc->flag_r + tid, ep);
    sync();
    TR(6);

    {
        uint32_t key[8];
#pragma unroll
        for (int i = 0; i < 8; i++) {
            const int j = warp * 256 + i * 32 + lane;
            const uint32_t u = __float_as_uint(__ldcg(sc->r + j) + 0.f);
            key[i] = (((u & 0x80000000u) ? ~u : (u | 0x80000000u)) & 0xffff0000u) | (uint32_t)(SEQ - j);
        }
#pragma unroll 1
        for (int k = 0; k < CAP; k++) {
            uint32_t b = key[0];
#pragma unroll
            for (int i = 1; i < 8; i++) b = max(b, key[i]);
            b = __reduce_max_sync(0xffffffffu, b);
#pragma unroll
            for (int i = 0; i < 8; i++) if (key[i] == b) key[i] = 0;
            if (lane == 0) asm volatile("st.shared.u32 [%0], %1;" ::"r"(cand + (warp * 8 + k) * 4), "r"(b) : "memory");
        }
    }
    sync();
    {
        uint32_t k0, k1, b = 0;
        asm volatile("ld.shared.v2.u32 {%0, %1}, [%2];" : "=r"(k0), "=r"(k1) : "r"(cand + lane * 8));
#pragma unroll 1
        for (int k = 0; k <= warp; k++) {
            b = __reduce_max_sync(0xffffffffu, max(k0, k1));
            if (k0 == b) k0 = 0;
            if (k1 == b) k1 = 0;
        }
        const int row = SEQ - (int)(b & 0xffffu);
        const uint2 st = load_stat(sc, row);
        uint4 v[3];
#pragma unroll
        for (int k = 0; k < 3; k++) v[k] = __ldg((const uint4*)(x + (size_t)row * DM) + min(lane + 32 * k, DM / 8 - 1));
#pragma unroll
        for (int k = 0; k < 3; k++) {
            const int i = lane + 32 * k;
            const float id = __uint_as_float(st.y);
            if (i < DM / 8)
                sts128(xs + (i >> 3) * 1024 + warp * 128 + (((i & 7) ^ warp) << 4), normalise(v[k].x, st.x, id), normalise(v[k].y, st.x, id),
                       normalise(v[k].z, st.x, id), normalise(v[k].w, st.x, id));
        }
        asm volatile("fence.proxy.async.shared::cta;" ::: "memory");
        if (lane == 0) {
            const float sg = bf_round(rcp(1.f + __expf(-__ldcg(sc->r + row))));
            asm volatile("st.shared.v2.b32 [%0], {%1, %2};" ::"r"(sig + warp * 8), "f"(sg), "r"(row) : "memory");
        }
    }
    sync();
    TR(7);

    {
        float acc[64];
        const int g = lane >> 2, t4 = lane & 3;
        auto block = [&](uint32_t a, uint32_t n, int step, int halves) {
#pragma unroll 1
            for (int i = 0; i < halves; i += 2, n += step) {
                const uint32_t s = n % FSLOT;
                mbar_wait(ffull + 8 * s, (n / FSLOT) & 1);
                const uint32_t a16 = (((a + i * 1024) & 0x3FFFFu) >> 4) | (1u << 16);
                const uint32_t b16 = ((ring + s * TILE_BYTES) & 0x3FFFFu) >> 4;
                auto mmas = [&](auto n_c) {
                    wg_fence();
#pragma unroll
                    for (int ks = 0; ks < decltype(n_c)::value; ks++)
                        wgmma_ss(acc, ((uint64_t)0x40000000u << 32) | (a16 + (ks >> 2) * 64 + (ks & 3) * 2), desc_nmajor(b16, ks), ks || i);
                    wg_commit();
                    wg_wait<0>();
                };
                if (i + 1 < halves) mmas(cint<8>());
                else mmas(cint<4>());
                if (lane == 0) mbar_arrive(fempty + 8 * s);
            }
            pin(acc);
        };
#pragma unroll 1
        for (int o = warp >> 2; o < nb; o += 2) {
            const bool pair = (o | 1) < nb;
            block(xs, 5 * (o & ~1) + (pair ? o & 1 : 0), pair ? 2 : 1, 10);
#pragma unroll
            for (int j = 0; j < 8; j++) {
                uint32_t h = pack_bf16(silu_f(bf_round(acc[4 * j])), silu_f(bf_round(acc[4 * j + 1])));
                asm("mul.rn.bf16x2 %0, %0, %1;" : "+r"(h) : "r"(pack_bf16(acc[32 + 4 * j], acc[33 + 4 * j])));
                asm volatile("st.shared.u32 [%0], %1;" ::"r"(hs + o * 1024 + g * 128 + ((j ^ g) << 4) + t4 * 4), "r"(h) : "memory");
            }
        }
        asm volatile("fence.proxy.async.shared::cta;" ::: "memory");
        sync();
        TR(8);
#pragma unroll 1
        for (int o = warp >> 2; o < 5; o += 2) {
            block(hs, 5 * nb + (o & ~1) * nkt + (o & 1), o < 4 ? 2 : 1, nb);
            if ((warp & 3) == 0) {
#pragma unroll
                for (int j = 0; j < 16; j++)
                    *(float2*)(sc->y + (e * CAP + g) * DM + o * 128 + j * 8 + t4 * 2) = make_float2(acc[4 * j], acc[4 * j + 1]);
            }
        }
    }
    sync();
    TR(9);
    if (tid == 0) flag_set(sc->flag_y + e, ep);
    if (tid < N_MOE) flag_wait(sc->flag_y + tid, ep);
    sync();
#pragma unroll 1
    for (int t = tid; t < 320; t += 256) {
        const int i = 2 * e * DM + t * 4;
        float4 y = __ldcg((const float4*)(sc->y + i));
#pragma unroll
        for (int j = 1; j < N_MOE; j++) {
            const float4 z = __ldcg((const float4*)(sc->y + j * CAP * DM + i));
            y.x += z.x; y.y += z.y; y.z += z.z; y.w += z.w;
        }
        float sg;
        int row;
        asm volatile("ld.shared.v2.b32 {%0, %1}, [%2];" : "=f"(sg), "=r"(row) : "r"(sig + (i / DM) * 8));
        const int o4 = (row * DM + i % DM) / 4;
        const uint2 v = __ldg((const uint2*)x + o4), st = load_stat(sc, row);
        uint32_t u0 = normalise(v.x, st.x, __uint_as_float(st.y)), u1 = normalise(v.y, st.x, __uint_as_float(st.y));
        asm("add.rn.bf16x2 %0, %0, %1;" : "+r"(u0) : "r"(pack_bf16(bf_round(y.x) * sg, bf_round(y.y) * sg)));
        asm("add.rn.bf16x2 %0, %0, %1;" : "+r"(u1) : "r"(pack_bf16(bf_round(y.z) * sg, bf_round(y.w) * sg)));
        sc->routed[i / 4] = make_uint2(silu2(u0), silu2(u1));
        if (i % DM == 0) sc->idx[i / DM] = row;
    }
    sync();
    TR(10);
    if (tid == 0) flag_set(sc->flag_u + e, ep);
}

__global__ void __launch_bounds__(384, 1)
fused_attn_kernel(const __nv_bfloat16* __restrict__ x, const __nv_bfloat16* __restrict__ wr,
                  __nv_bfloat16* __restrict__ out, Scratch* sc,
                  const __grid_constant__ CUtensorMap tm_x, const __grid_constant__ CUtensorMap tm_wq,
                  const __grid_constant__ CUtensorMap tm_k, const __grid_constant__ CUtensorMap tm_v,
                  const __grid_constant__ CUtensorMap tm_wo, const __grid_constant__ CUtensorMap tm_g,
                  const __grid_constant__ CUtensorMap tm_u, const __grid_constant__ CUtensorMap tm_d) {
    PT(0);
    extern __shared__ __align__(16) uint8_t smem_raw[];
    const uint32_t ring = smem_u32(smem_raw);
    const uint32_t stash = ring + NSLOT * TILE_BYTES;
    const uint32_t bars = stash + 3 * TILE_BYTES;
    const uint32_t full = bars, empty = bars + 32;
    const uint32_t xfull = bars + 64;
    const uint32_t rfull = bars + 144;
    const uint32_t rdone = bars + 288;
    const uint32_t vacant = bars + 336, routed = bars + 344, xgfull = bars + 352, gated = bars + 360;
    const uint32_t soon = bars + 376, qfull = bars + 384, epv = bars + 392;
    const uint32_t epoch = bars + 368;
    [[maybe_unused]] const uint32_t trbuf = bars + 400;
    const uint32_t ffull = rfull, fempty = rfull + 8 * FSLOT, qdone = rdone, h1done = rdone + 32, wperm = trbuf;

    const int warp = __shfl_sync(0xffffffffu, threadIdx.x >> 5, 0), wg = warp >> 2;
    const int rank = blockIdx.x & 1;
    const int cl = blockIdx.x >> 1;
    const int r7 = ((cl - 36) * 37) >> 8;
    const int qp = cl < 36 ? (cl < 4 ? 0 : (cl - 4) & 7) : cl - 35 - 7 * r7;
    const int grp = cl < 4 ? cl + 4 : cl < 36 ? (cl - 4) >> 3 : r7 + 4;
    const bool helper = blockIdx.x >= N_MAIN;
    const int qt = helper ? (blockIdx.x - N_MAIN) * 4 : qp * 2 + rank;

    auto load_x = [&](int w, int i, int tile) {
        const uint32_t bar = xfull + (w * 5 + i) * 8;
        mbar_expect_tx(bar, 16384);
        tma_3d(ring + (i == 4 ? 2 : 3 + i) * TILE_BYTES + w * 16384, &tm_x, bar, 0, tile * 128 + w * 64, i == 0 ? 8 : 2 * i - 2);
    };
    if (warp == 4) {
        if (elect_one()) {
#pragma unroll
            for (int i = 0; i < 10; i++) mbar_init(xfull + 8 * i, 1);
#pragma unroll
            for (int i = 0; i < XN; i++) load_x(i & 1, i >> 1, qt);
            asm volatile("fence.mbarrier_init.release.cluster;" ::: "memory");
        }
        __syncwarp();
    }
    PT(6);
    if ((ring & 0xFFFFFFu) != RING_OFFSET) return;
    PT(7);
    if (warp >= 5 && elect_one()) {
        if (warp == 5) {
#pragma unroll
            for (int i = 0; i < NSLOT; i++) { mbar_init(full + 8 * i, 1); mbar_init(empty + 8 * i, 16); }
        } else if (warp == 6) {
#pragma unroll
            for (int i = 0; i < 6; i++) mbar_init(rdone + 8 * i, helper ? 8 : 4);
        } else if (warp == 7) {
            mbar_init(vacant, 8); mbar_init(routed, 32); mbar_init(xgfull, 1); mbar_init(gated, 8); mbar_init(soon, 1);
            mbar_init(qfull, 1); mbar_init(epv, 1);
        } else if (warp == 8) {
            asm volatile("prefetch.tensormap [%0];" ::"l"(&tm_wq) : "memory");
        } else {
#pragma unroll
            for (int i = 0; i < 6; i++) mbar_init(rfull + ((warp - 9) * 6 + i) * 8, helper && warp == 10 ? 4 : 1);
        }
        asm volatile("fence.mbarrier_init.release.cluster;" ::: "memory");
    }
    __syncwarp();
    PT(1);
    asm volatile("barrier.cluster.arrive.relaxed.aligned;" ::: "memory");
    if (warp == 4) {
        if (elect_one()) {
#pragma unroll
            for (int i = XN; i < 10; i++) load_x(i & 1, i >> 1, qt);
        }
        __syncwarp();
    }

    if (wg == 2) {
        asm volatile("setmaxnreg.dec.sync.aligned.u32 24;");
        asm volatile("barrier.cluster.wait.aligned;" ::: "memory");
        uint32_t lane;
        asm volatile("mov.u32 %0, %%laneid;" : "=r"(lane));
        PT(2);
        if (warp == 8 && helper) {
          if (elect_one()) {
            mbar_arrive(full + 16);
#pragma unroll 1
            for (int t = 0; t < 4; t++) {
#pragma unroll 1
                for (int i = 0; i < 20; i++) {
                    const int s = i % 3;
                    mbar_wait(empty + 8 * s, ((t + (i + 1) / 3) & 1) ^ 1);
                    mbar_expect_tx(full + 8 * s, TILE_BYTES);
                    tma_2d_mc(ring + s * TILE_BYTES + rank * 16384, &tm_wq, full + 8 * s, (((i / 5) * 2 + rank) * 4 + 3) * 128 + 64,
                              ((i + 4) % 5) * 128);
                    if (t == 0 && i == 2) {
                        asm volatile("nanosleep.u32 1500;");
#pragma unroll 1
                        for (int k = 3 + ((blockIdx.x >> 1) & 1); k < 20; k += 2) tma_prefetch(&tm_wq, (((k / 5) * 2 + rank) * 4 + 3) * 128 + 64, ((k + 4) % 5) * 128);
                    }
                    if (i == 2 && t < 3) {
#pragma unroll 1
                        for (int k = 2; k < 8; k++) load_x(k & 1, k >> 1, qt + t + 1);
                    }
                    if (i == 18 && t < 3) {
                        mbar_wait(empty + 24, t & 1);
                        load_x(0, 0, qt + t + 1); load_x(1, 0, qt + t + 1);
                    }
                }
                if (t < 3) {
                    mbar_wait(empty + 16, t & 1);
                    mbar_arrive(full + 16);
                    load_x(0, 4, qt + t + 1); load_x(1, 4, qt + t + 1);
                }
            }
            const int e = blockIdx.x - N_MAIN, nb = e == N_MOE - 1 ? 6 : 7, nkt = (nb + 1) >> 1;
            mbar_wait(h1done, 0);
            uint32_t s = 0, ph = 1;
#pragma unroll 1
            for (int o0 = 0, w; o0 < nb + 5; o0 += w) {
                const bool up = o0 < nb;
                w = o0 + 1 < (up ? nb : nb + 5) ? 2 : 1;
#pragma unroll 1
                for (int k = 0; k < (up ? 5 : nkt) * w; k++) {
                    const int o = o0 + (k & (w - 1)), i = k >> (w - 1);
                    mbar_wait(fempty + 8 * s, ph);
                    mbar_expect_tx(ffull + 8 * s, TILE_BYTES);
                    const int c0 = up ? (e * 7 + o) * 64 : (o - nb) * 128, c1 = (up ? 0 : e * 448) + i * 128;
                    tma_2d(ring + s * TILE_BYTES, up ? &tm_g : &tm_d, ffull + 8 * s, c0, c1);
                    tma_2d(ring + s * TILE_BYTES + 16384, up ? &tm_u : &tm_d, ffull + 8 * s, up ? c0 : c0 + 64, c1);
                    if (++s == FSLOT) { s = 0; ph ^= 1; }
                }
            }
          }
        } else if (warp == 8) {
          if (elect_one()) {
            PT(3);
            mbar_arrive(full + 16);
            mbar_arrive(full + 24);
            auto coords = [&](int i, const CUtensorMap*& tm, int& c0, int& c1) {
                c0 = rank * 64;
                if (i < 20) {
                    const int ps = i / 5;
                    tm = &tm_wq; c1 = (i % 5 < 3 ? i % 5 : 7 - i % 5) * 128;
                    if (ps == 1) {
                        c0 = 0;
                        c1 = (i == 5 ? rank : i == 6 ? 2 : 4 - rank) * 128;
                    }
                    c0 += (grp * 4 + (ps < 2 ? 2 + ps : 3 - ps)) * 128;
                } else if (i < 148) {
                    const int u = i - 20;
                    const bool isk = (u == 0) || ((u & 1) && u != 127);
                    const int b = isk ? (u + 1) >> 1 : (u == 127 ? 63 : (u >> 1) - 1);
                    tm = isk ? &tm_k : &tm_v; c1 = (grp * 64 + b) * 128;
                } else {
                    tm = &tm_wo; c0 = (i < 152 ? ((i - 132) >> 1) ^ (grp >> 2) : (grp + ((i - 150) >> 1)) & 7) * 64; c1 = (grp * 4 + (i & 1) * 2 + rank) * 128;
                }
            };
#pragma unroll 1
            for (int i = 0; i < 168; i++) {
                const CUtensorMap* tm;
                int c0, c1;
                if (i == 8) i = 10;
                const int a = i < 8 ? i : i - 2;
                const int s = i < 20 ? a % 3 : (i & 3);
                const uint32_t ph = i < 20 ? ((a + 1) / 3) & 1 : ((i >> 2) & 1) ^ (s < 2);
                coords(i, tm, c0, c1);
                if (i == QAT) mbar_wait(qfull, 0);
                mbar_wait(empty + 8 * s, ph ^ 1);
                if (i == 6) {
                    mbar_expect_tx(full + 8 * s, TILE_BYTES / 2);
                    if (rank == 0) tma_2d_mc(ring + s * TILE_BYTES, tm, full + 8 * s, c0, c1);
                } else {
                    mbar_expect_tx(full + 8 * s, TILE_BYTES);
                    tma_2d_mc(ring + s * TILE_BYTES + rank * 16384, tm, full + 8 * s, c0, c1);
                }
                if (i == 140) mbar_arrive(soon);
                if (i >= 163 && i < 167) {
                    if (i == 163) {
                        TL(0);
                        mbar_wait(routed, 0);
                        asm volatile("fence.proxy.async.global;" ::: "memory");
                        TL(1);
                        mbar_expect_tx(xgfull, TILE_BYTES);
                    }
                    asm volatile("cp.async.bulk.shared::cluster.global.mbarrier::complete_tx::bytes [%0], [%1], 8192, [%2];"
                                 ::"r"(stash + 3 * 16384 + (i - 163) * 8192), "l"(sc->gate + blockIdx.x * 2560 + (i - 163) * 512), "r"(xgfull) : "memory");
                }
                if (i == 12) asm volatile("prefetch.tensormap [%0];\nprefetch.tensormap [%1];" ::"l"(&tm_k), "l"(&tm_v) : "memory");
                if (i == 140) asm volatile("prefetch.tensormap [%0];" ::"l"(&tm_wo) : "memory");
                if (i >= GPF && i < GPF + 10)
                    asm volatile("cp.async.bulk.prefetch.L2.global [%0], 4096;" ::"l"(sc->gate + blockIdx.x * 2560 + (i - GPF) * 256) : "memory");
                const int j = i < 2 ? 2 + i : i == 2 ? 4 + ((qp - 4) & 7) : i + 9;
                if (j < 168 && (j & 7) == qp && (j & ~1) != 8) {
                    coords(j, tm, c0, c1);
                    tma_prefetch(tm, c0, c1);
                }
            }
            sc->epoch[blockIdx.x] += 1;
          }
        } else if (warp == 9) {
            const uint32_t ep = sc->epoch[blockIdx.x] + 1;
            if (helper) {
#pragma unroll 1
                for (int t = 0; t < 4; t++) {
                    if (t == 3) {
                        mbar_wait_sleep(qdone + 40, 0);
                        if (lane == 0) flag_set(sc->flag_r + (blockIdx.x - N_MAIN), ep);
                    }
                    mbar_wait_sleep(qdone + 8 * t, 0);
                    if (lane == 0) flag_set(sc->flag_q + qt + t, ep);
                }
                if (lane == 0) sc->epoch[blockIdx.x] = ep;
            } else {
                mbar_wait_sleep(gated, 0);
                flag_wait<300>(sc->flag_q + qt, ep);
                asm volatile("fence.proxy.async.global;" ::: "memory");
                if (lane == 0) mbar_expect_tx(qfull, 16384);
                __syncwarp();
                if (lane < 8)
                    asm volatile("cp.async.bulk.shared::cluster.global.mbarrier::complete_tx::bytes [%0], [%1], 2048, [%2];"
                                 ::"r"(stash + 2 * TILE_BYTES + lane * 4096 + 2048),
                                   "l"(sc->qoff + ((qt * 4 + (grp >> 1)) * 8 + lane) * 256 + (grp & 1) * 128), "r"(qfull) : "memory");
            }
        } else if (helper) {
        } else if (warp == 10) {
            const uint32_t ep = sc->epoch[blockIdx.x] + 1;
            if (lane == 0) {
                asm volatile("st.shared.u32 [%0], %1;" ::"r"(epoch), "r"(ep) : "memory");
                mbar_arrive(epv);
            }
            mbar_wait_sleep(gated, 0);
            flag_wait<400>(sc->flag_u + (lane & 3), ep);
            __syncwarp();
            const int rrow = __ldcg(sc->idx + (lane & 7));
            uint32_t hit = __ballot_sync(0xffffffffu, lane < 8 && (rrow >> 7) == qt);
            while (hit) {
                const int k = __ffs(hit) - 1, row = __shfl_sync(0xffffffffu, rrow, k);
                hit &= hit - 1;
#pragma unroll 1
                for (int i = lane; i < 40; i += 32) {
                    const int th = ((row >> 4) & 7) * 32 + (row & 7) * 4 + (i & 3);
                    ((uint32_t*)sc->gate)[(((blockIdx.x * 5 + (i >> 3)) * 2 + 1) * 256 + th) * 4 + ((i >> 1) & 2) + ((row >> 3) & 1)] =
                        __ldcg((const uint32_t*)sc->routed + k * (DM / 2) + (i < 32 ? grp * 32 + i : 224 + grp * 8 + i));
                }
            }
            mbar_arrive(routed);
        } else if (warp == 11) {
            const uint32_t ep = sc->epoch[blockIdx.x] + 1;
            const uint32_t unit = lane < 16 ? lane >> 3 : (lane >> 1) - 6;
            const uint32_t ofs = (lane & 1) * 8192 + (lane < 16 ? ((lane >> 1) & 3) * 2048 : 0);
            if (lane < 18) mbar_expect_tx(rfull + 8 * lane, 8192);
            mbar_wait_sleep(soon, 0);
            uint32_t done = lane >= 30, spins = 0;
            do {
                if (!done) {
                    uint4 v;
                    asm volatile("ld.relaxed.gpu.global.v4.u32 {%0, %1, %2, %3}, [%4];" : "=r"(v.x), "=r"(v.y), "=r"(v.z), "=r"(v.w)
                                 : "l"(sc->flag + (qt * 8 + grp) * 32 + lane) : "memory");
                    uint32_t ok = v.x == ep && v.y == ep && v.z == ep && v.w == ep;
                    if (ok)
                        asm volatile("{\n.reg .pred p;\nmbarrier.test_wait.parity.shared::cta.b64 p, [%1], 0;\nselp.u32 %0, 1, 0, p;\n}\n"
                                     : "=r"(ok) : "r"(unit >= 6 ? rdone + (lane - 24) * 8 : vacant) : "memory");
                    done = ok;
                    if (ok)
                        asm volatile("cp.async.bulk.shared::cluster.global.mbarrier::complete_tx::bytes [%0], [%1], %2, [%3];"
                                     ::"r"(stash + (unit >= 6 ? unit - 6 : unit) * 16384 + ofs),
                                       "l"((const char*)sc->part + ((qt * 8 + grp) * 9 + unit) * 16384 + ofs), "r"(lane < 16 ? 2048 : 8192),
                                       "r"(rfull + 16 * unit + 8 * (lane & 1)) : "memory");
                }
                if (++spins > 4000000u) __trap();
            } while (!__all_sync(0xffffffffu, done));
        }
    } else {
        asm volatile("setmaxnreg.inc.sync.aligned.u32 240;");
        const uint32_t lane = threadIdx.x & 31;
        PT(2);
        asm volatile("barrier.cluster.wait.aligned;" ::: "memory");
        PT(3);
        const int my_bar = 1 + wg, other_bar = 2 - wg;
        const uint32_t my_stash = stash + warp * 4096 + lane * 16;
        constexpr uint32_t T16 = TILE_BYTES / 16;
        constexpr uint32_t ring16 = RING_OFFSET >> 4;
        uint32_t rel = 0;
        if (lane < 2)
            asm("mapa.shared::cluster.u32 %0, %1, %2;" : "=r"(rel) : "r"(empty), "r"(lane));
        rel = opaque(rel);

        const int zero = gridDim.y - 1;
        PT(4);

        uint32_t q[32];
        float acc[64];
        float wsum;
        uint32_t ep_tag;
        uint2 st0, st1;
        auto project = [&](auto helper_c, int job) {
            constexpr bool HELPER = decltype(helper_c)::value;
            float (&acc32)[32] = *reinterpret_cast<float (*)[32]>(&acc[0]);
            const int tile = qt + job;
            uint32_t lane = threadIdx.x & 31;
            if (HELPER) asm volatile("mov.u32 %0, %%laneid;" : "=r"(lane));
            uint32_t xa[128];
            const uint32_t lm_off = wg * 16384 + ((warp & 3) * 16 + (lane & 15)) * 128 + (((lane >> 4) ^ (lane & 7)) << 4);
            float sm[4][4] = {}, sq[4][4] = {};
            constexpr uint32_t ONES = 0x3f803f80u;
            constexpr float SC = 0.08838834764831845f * 1.4426950408889634f;
            auto squares = [&](const uint32_t* a) {
#pragma unroll
                for (int r = 0; r < 4; r++) hmma8(sq[r], a[r & 2], a[(r & 2) + 1], a[r]);
            };
            const int row = tile * 128 + warp * 16 + (lane >> 2);
            auto load_stats = [&](int t) {
                asm volatile("ld.relaxed.gpu.global.v2.u32 {%0, %1}, [%4];\nld.relaxed.gpu.global.v2.u32 {%2, %3}, [%4 + 64];"
                             : "=r"(st0.x), "=r"(st0.y), "=r"(st1.x), "=r"(st1.y) : "l"(sc->stat + t * 128 + warp * 16 + (lane >> 2)) : "memory");
            };
            uint32_t mm0, mm1;
            float rd0, rd1;
            if (HELPER && job == 0) load_stats(tile);
#pragma unroll
            for (int i = 0; i < 5; i++) {
                mbar_wait(xfull + (wg * 5 + i) * 8, HELPER ? job & 1 : 0);
                if (i == 0) PT(5);
                if (HELPER && i == 0) TR(20 + job * 8);
                if (HELPER && i == 4) TR(20 + job * 8 + 7);
                if (HELPER && job == 1) TR(110 + i);
                const uint32_t base = ring + (i == 4 ? 2 : 3 + i) * TILE_BYTES + lm_off;
                uint32_t* a = xa + (i == 0 ? 96 : 32 * (i - 1));
#pragma unroll
                for (int ks = 0; ks < 8; ks++)
                    ldsm4((base ^ ((ks & 3) << 5)) + (ks >> 2) * 8192, a[4 * ks], a[4 * ks + 1], a[4 * ks + 2], a[4 * ks + 3]);
                if (i == 4) PT(9);
                uint32_t wb[16];
#pragma unroll
                for (int ks = 0; ks < 8; ks++) {
                    wb[2 * ks] = ONES; wb[2 * ks + 1] = ONES;
                    if (HELPER)
                        asm volatile("ld.shared.v2.u32 {%0, %1}, [%2];" : "=r"(wb[2 * ks]), "=r"(wb[2 * ks + 1]) : "r"(wperm + (lane & 3) * 8 + ((i == 0 ? 32 : 8 * i - 8) + ks) * 32));
                }
#pragma unroll
                for (int ks = 0; ks < 8; ks++) {
                    hmma(sm[ks & 3], a[4 * ks], a[4 * ks + 1], a[4 * ks + 2], a[4 * ks + 3], wb[2 * ks], wb[2 * ks + 1]);
                    if (!HELPER && i < 4) squares(a + 4 * ks);
                }
                if (HELPER && i == 0) {
                    uint32_t spins = 0;
                    while (__any_sync(0xffffffffu, ((st0.x ^ ep_tag) | (st1.x ^ ep_tag)) >> 16) && ++spins < 2000000u) load_stats(tile);
                    mm0 = __byte_perm(st0.x, 0, 0x1010); mm1 = __byte_perm(st1.x, 0, 0x1010);
#pragma unroll
                    for (int ks = 0; ks < 8; ks++)
                        stsm4((base ^ ((ks & 3) << 5)) + (ks >> 2) * 8192, bf2_sub(a[4 * ks], mm0), bf2_sub(a[4 * ks + 1], mm1),
                              bf2_sub(a[4 * ks + 2], mm0), bf2_sub(a[4 * ks + 3], mm1));
                    asm volatile("fence.proxy.async.shared::cta;" ::: "memory");
                }
            }
            release_at<16>(rel);
            sched_fence(zero);
            const float m0 = ((sm[0][0] + sm[1][0]) + (sm[2][0] + sm[3][0])) * (HELPER ? 1.f : 1.f / DM);
            const float m1 = ((sm[0][2] + sm[1][2]) + (sm[2][2] + sm[3][2])) * (HELPER ? 1.f : 1.f / DM);
            if (HELPER) {
                const float id0 = __uint_as_float(st0.y), id1 = __uint_as_float(st1.y);
                rd0 = SC * id0; rd1 = SC * id1;
                if ((lane & 3) == 0) {
                    sc->r[row] = bf_round((m0 - bf_lo(mm0) * wsum) * id0);
                    sc->r[row + 8] = bf_round((m1 - bf_lo(mm1) * wsum) * id1);
                }
                __syncwarp();
                if (job == 3 && lane == 0) mbar_arrive(qdone + 40);
            } else {
                mm0 = pack_bf16(m0, m0); mm1 = pack_bf16(m1, m1);
            }
            auto centre = [&](int kt) {
#pragma unroll
                for (int i = 32 * kt; i < 32 * kt + 32; i++) asm volatile("sub.rn.bf16x2 %0, %0, %1;" : "+r"(xa[i]) : "r"((i & 1) ? mm1 : mm0));
            };
            if (!HELPER) {
#pragma unroll
                for (int ks = 0; ks < 8; ks++) squares(xa + 96 + 4 * ks);
            }
            if (!HELPER) centre(0);
            if (wg == 1) bar_arrive(1);
            auto diag = [&](int r, int h) { return (lane & 4) ? sq[r][h + 1] + sq[r + 2][h + 1] : sq[r][h] + sq[r + 2][h]; };
            auto spread = [&](float v) { return __shfl_sync(0xffffffffu, v, (lane & ~3u) | (lane >> 3)) * (1.f / DM); };
            if (!HELPER) { rd0 = diag(0, 0); rd1 = diag(1, 2); }
            PT(10);

            if (HELPER) TR(20 + job * 8 + 1);
            uint32_t qs = 0, qph = HELPER ? job & 1 : 0;
            uint4 gx;
            if (HELPER) {
#pragma unroll
                for (int i = 0; i < 64; i++) acc[i] = 0.f;
            }
            const uint32_t xs16 = ring16 + 3 * T16 + wg * 1024;
            constexpr int SS = HELPER ? 0 : 3;
#pragma unroll 1
            for (int pass = 0;; pass++) {
                const uint32_t hs = my_stash + (pass == 2 ? 0 : pass + 1) * TILE_BYTES;
                uint4* const dst = sc->qoff + ((tile * 4 + pass) * 8 + warp) * 256 + lane;
                auto put = [&](int lo) {
#pragma unroll
                    for (int i = lo; i < lo + 4; i++) {
                        const uint4 v = make_uint4(pack_bf16(acc[8 * i] * rd0, acc[8 * i + 1] * rd0), pack_bf16(acc[8 * i + 2] * rd1, acc[8 * i + 3] * rd1),
                                                   pack_bf16(acc[8 * i + 4] * rd0, acc[8 * i + 5] * rd0), pack_bf16(acc[8 * i + 6] * rd1, acc[8 * i + 7] * rd1));
                        if (HELPER) dst[i * 32] = v;
                        else sts128(hs + i * 512, v.x, v.y, v.z, v.w);
                        if (i == 2 || i == 5) sched_fence(zero);
                    }
                };
                auto gate_load = [&](int j) {
                    const uint32_t* src = (const uint32_t*)x + (qt * 128 + warp * 16 + (lane >> 2)) * (DM / 2) + (lane & 3) +
                                          (j < 4 ? grp * 32 + j * 8 : 256 + grp * 8);
                    asm volatile("ld.global.nc.u32 %0, [%4];\nld.global.nc.u32 %1, [%4 + %5];\n"
                                 "ld.global.nc.u32 %2, [%4 + 16];\nld.global.nc.u32 %3, [%4 + %5 + 16];"
                                 : "=r"(gx.x), "=r"(gx.y), "=r"(gx.z), "=r"(gx.w) : "l"(src), "n"(8 * DM * 2));
                };
                auto gate_store = [&](int j) {
                    const float id0 = rd0 * (1.f / SC), id1 = rd1 * (1.f / SC);
                    uint4* g = sc->gate + (blockIdx.x * 5 + j) * 512 + threadIdx.x;
                    g[0] = gx;
                    g[256] = make_uint4(silu2_ln(normalise(gx.x, mm0, id0)), silu2_ln(normalise(gx.y, mm1, id1)),
                                        silu2_ln(normalise(gx.z, mm0, id0)), silu2_ln(normalise(gx.w, mm1, id1)));
                };
                auto advance = [&] {
                    const uint32_t r = rel ? rel + 8 * qs : 0;
                    if (++qs == 2) qph ^= 1;
                    if (qs == 3) qs = 0;
                    return r;
                };
                if (!HELPER && pass == 1) {
#pragma unroll
                    for (int turn = 0; turn < 3; turn++) {
                        if (turn) mbar_wait(full + 8 * qs, qph);
                        bar_sync(my_bar);
                        const uint32_t tile16 = ring16 + qs * T16;
                        wg_fence();
#pragma unroll
                        for (int ks = 0; ks < (turn == 1 ? 8 : 16); ks++) {
                            const uint32_t* a = xa + (turn == 2 ? 64 : turn * 64) + 4 * ks;
                            if (turn == 2 && ks < 8) wgmma_ss64(acc32, desc_kmajor(xs16 - (ks >> 2) * 512, ks), desc_nmajor(tile16, ks), 1);
                            else wgmma_rs64(acc32, a[0], a[1], a[2], a[3], desc_nmajor(tile16, ks), turn || ks);
                        }
                        wg_commit();
                        bar_arrive(other_bar);
                        if (turn == 0) gate_load(4);
                        if (turn == 1) gate_store(4);
                        const uint32_t rl = advance();
                        if (turn == 2) mbar_wait(full + 8 * qs, qph);
                        wg_wait<0>();
                        TA(5 + 2 * turn);
                        release_at<0>(rl);
                    }
                    pin(acc32);
                    put(0);
                    continue;
                }
                uint32_t rl = 0;
#pragma unroll
                for (int kt = 0; kt < 5; kt++) {
                    const bool takes = !HELPER || kt == 0 || kt == 2 || kt == 3, passes = !HELPER || kt == 1 || kt == 2 || kt == 4;
                    if (kt != 0 || pass == 0) mbar_wait(full + 8 * qs, qph);
                    if (takes) bar_sync(my_bar);
                    const uint32_t tile16 = ring16 + qs * T16;
                    wg_fence();
                    if (kt != SS) {
                        mma_tile<1>(acc, xa + (kt < SS ? kt : kt - 1) * 32, tile16, kt != 0);
                    } else {
#pragma unroll
                        for (int ks = 0; ks < 8; ks++) wgmma_ss(acc, desc_kmajor(xs16 - (ks >> 2) * 512, ks), desc_nmajor(tile16, ks), kt || ks);
                        wg_commit();
                    }
                    if (passes && !(HELPER && kt == 4 && pass == 3 && wg == 1)) bar_arrive(other_bar);
                    if (HELPER && pass == 0 && kt < 4) centre(kt);
                    if (!HELPER && pass == 0 && kt < 3) {
#pragma unroll
                        for (int ks = 3 * kt; ks < 3 * kt + 3 && ks < 8; ks++) {
                            const uint32_t ad = ((ring + 3 * TILE_BYTES + lm_off) ^ ((ks & 3) << 5)) + (ks >> 2) * 8192;
                            uint32_t a, b, c, d;
                            ldsm4(ad, a, b, c, d);
                            stsm4(ad, bf2_sub(a, mm0), bf2_sub(b, mm1), bf2_sub(c, mm0), bf2_sub(d, mm1));
                        }
                        if (kt == 2) asm volatile("fence.proxy.async.shared::cta;" ::: "memory");
                    }
                    if (HELPER && kt == 2 && pass == 3 && job < 3) load_stats(tile + 1);
                    if (!HELPER && pass >= 2 && kt < 4) {
                        if (kt & 1) gate_store((pass - 2) * 2 + (kt >> 1));
                        else gate_load((pass - 2) * 2 + (kt >> 1));
                    }
                    const uint32_t rl_prev = rl;
                    rl = advance();
                    if (!passes) continue;
                    if (HELPER && kt != 2) {
                        wg_wait<1>();
                        if (job == 1) TR(120 + pass * 5 + kt - 1);
                        release_at<0>(rl_prev);
                        if (kt == 1 && pass == 3) release_at<24>(rel);
                    }
                    if (kt == 4 && !(HELPER && pass == 3)) mbar_wait(full + 8 * qs, qph);
                    wg_wait<0>();
                    if (!HELPER) TA(pass * 5 + kt);
                    if (HELPER && job == 1) TR(120 + pass * 5 + kt);
                    release_at<0>(rl);
                    if (!HELPER && kt < 3 && pass == 0) centre(kt + 1);
                    if (!HELPER && kt == 3 && pass == 0) {
                        float v0 = spread(rd0) - m0 * m0, v1 = spread(rd1) - m1 * m1;
                        if (RARE(__any_sync(0xffffffffu, !(m0 * m0 <= 256.f * v0 && m1 * m1 <= 256.f * v1)))) {
                            const uint4* xr = (const uint4*)x + row * (DM / 8) + (lane & 3);
                            v0 = 0.f; v1 = 0.f;
#pragma unroll 1
                            for (int i = 0; i < DM / 32; i++) {
                                const uint4 a = __ldg(xr + 4 * i), b = __ldg(xr + DM + 4 * i);
                                const uint32_t w[8] = {a.x, a.y, a.z, a.w, b.x, b.y, b.z, b.w};
#pragma unroll
                                for (int k = 0; k < 8; k++) {
                                    const uint32_t d = bf2_sub(w[k], k < 4 ? mm0 : mm1);
                                    float& v = k < 4 ? v0 : v1;
                                    v = fmaf(bf_lo(d), bf_lo(d), fmaf(bf_hi(d), bf_hi(d), v));
                                }
                            }
#pragma unroll
                            for (int d = 1; d <= 2; d <<= 1) { v0 += __shfl_xor_sync(0xffffffffu, v0, d); v1 += __shfl_xor_sync(0xffffffffu, v1, d); }
                            v0 *= 1.f / DM; v1 *= 1.f / DM;
                            const float e0 = m0 - bf_lo(mm0), e1 = m1 - bf_lo(mm1);
                            v0 -= e0 * e0; v1 -= e1 * e1;
                        }
                        const float id0 = inv_den(fmaxf(v0, 0.f)), id1 = inv_den(fmaxf(v1, 0.f));
                        rd0 = SC * id0; rd1 = SC * id1;
                        if (warp == grp) {
                            mbar_wait(epv, 0);
                            uint32_t tg;
                            asm volatile("ld.shared.u32 %0, [%1];" : "=r"(tg) : "r"(epoch));
                            if ((lane & 3) == 0)
                                asm volatile("st.relaxed.gpu.global.v2.u32 [%0], {%1, %2};\nst.relaxed.gpu.global.v2.u32 [%0 + 64], {%3, %4};"
                                             ::"l"(sc->stat + row), "r"(__byte_perm(mm0, tg, 0x5410)), "f"(id0), "r"(__byte_perm(mm1, tg, 0x5410)), "f"(id1) : "memory");
                        }
                    }
                }
                pin(acc);
                if (!HELPER && pass == 3) break;
                put(0);
                put(4);
                if (HELPER) TR(20 + job * 8 + 2 + pass);
                if (HELPER && pass == 3) {
                    __syncwarp();
                    if (lane == 0) mbar_arrive(qdone + 8 * job);
                    return;
                }
            }
            release_at<24>(rel);
            if (lane == 0) mbar_arrive(gated);
#pragma unroll
            for (int i = 0; i < 32; i++) {
                const float r = (i & 1) ? rd1 : rd0;
                q[i] = pack_bf16(acc[2 * i] * r, acc[2 * i + 1] * r);
            }
        };
        if (helper) {
            const uint32_t ep = sc->epoch[blockIdx.x] + 1;
            if (threadIdx.x < 160) {
                const uint32_t* w32 = (const uint32_t*)wr + (threadIdx.x >> 2) * 8 + (threadIdx.x & 3);
                asm volatile("st.shared.v2.u32 [%0], {%1, %2};" ::"r"(wperm + threadIdx.x * 8), "r"(__ldg(w32)), "r"(__ldg(w32 + 4)) : "memory");
            }
            asm volatile("bar.sync 3, 256;" ::: "memory");
            float ws[4] = {};
#pragma unroll 4
            for (int ks = 0; ks < 40; ks++) {
                uint32_t b0, b1;
                asm volatile("ld.shared.v2.u32 {%0, %1}, [%2];" : "=r"(b0), "=r"(b1) : "r"(wperm + (lane & 3) * 8 + ks * 32));
                hmma(ws, 0x3f803f80u, 0x3f803f80u, 0x3f803f80u, 0x3f803f80u, b0, b1);
            }
            wsum = ws[0];
            ep_tag = ep << 16;
            TR(0);
#pragma unroll 1
            for (int job = 0; job < 4; job++) {
                project(cint<1>(), job);
                TR(1 + job);
            }
            if (elect_one()) mbar_arrive(h1done);
            ffn_role(sc, ring, ffull, fempty, blockIdx.x - N_MAIN, ep, warp, x);
            return;
        }
        project(cint<0>(), 0);
        TR(2);
        TG(112);

        float o[64];
        uint32_t p[32];
        float l0, l1;
        float sg0 = 0.f, sg1 = 0.f;
        constexpr float L_LO = 9.313225746154785e-10f, L_HI = 1.152921504606847e18f;
        float l_hi = L_HI;
        float (&s)[64] = acc;

        auto exp_range = [&](const float (&s)[64], int lo, int hi, float& u0, float& u1) {
            float w0 = 0.f, w1 = 0.f;
#pragma unroll
            for (int i = lo; i < hi; i += 4) {
                const float e0 = ex2(s[i]), e1 = ex2(s[i + 1]), e2 = ex2(s[i + 2]), e3 = ex2(s[i + 3]);
                u0 += e0; u1 += e2;
                if (i == lo) { w0 = e1; w1 = e3; } else { w0 += e1; w1 += e3; }
                p[i / 2] = pack_bf16(e0, e1); p[i / 2 + 1] = pack_bf16(e2, e3);
            }
            u0 += w0; u1 += w1;
        };
        auto unsafe = [&](bool first, float u0, float u1) {
            return (bool)__any_sync(0xffffffffu, !(u0 + u1 <= l_hi) || (first && !(fminf(u0, u1) >= L_LO)));
        };
        auto softmax_true_max = [&](const float (&s)[64], bool first, float b0, float b1, float& u0, float& u1) {
            uint32_t t;
            asm volatile("mov.u32 %0, %%tid.x;" : "=r"(t));
            uint4* const st = sc->rare + blockIdx.x * (16 * 256) + t;
            auto ld = [](const uint4* a) {
                uint4 v;
                asm volatile("ld.global.v4.u32 {%0, %1, %2, %3}, [%4];" : "=r"(v.x), "=r"(v.y), "=r"(v.z), "=r"(v.w) : "l"(a) : "memory");
                return v;
            };
#pragma unroll
            for (int i = 0; i < 16; i++)
                asm volatile("st.global.v4.f32 [%0], {%1, %2, %3, %4};" ::"l"(st + i * 256), "f"(s[4 * i]), "f"(s[4 * i + 1]), "f"(s[4 * i + 2]), "f"(s[4 * i + 3]) : "memory");
            float a0 = s[0], a1 = s[2];
#pragma unroll 1
            for (int i = 0; i < 16; i++) {
                const uint4 v = ld(st + i * 256);
                a0 = fmaxf(a0, fmaxf(__uint_as_float(v.x), __uint_as_float(v.y)));
                a1 = fmaxf(a1, fmaxf(__uint_as_float(v.z), __uint_as_float(v.w)));
            }
            float t0 = b0, t1 = b1;
#pragma unroll
            for (int d = 1; d <= 2; d <<= 1) {
                a0 = fmaxf(a0, __shfl_xor_sync(0xffffffffu, a0, d)); a1 = fmaxf(a1, __shfl_xor_sync(0xffffffffu, a1, d));
                t0 += __shfl_xor_sync(0xffffffffu, t0, d); t1 += __shfl_xor_sync(0xffffffffu, t1, d);
            }
            if (!first) {
                a0 = fmaxf(a0, l_hi < 0.f ? sg0 : __log2f(t0)); a1 = fmaxf(a1, l_hi < 0.f ? sg1 : __log2f(t1));
            }
            const float al0 = first ? 1.f : ex2(sg0 - a0), al1 = first ? 1.f : ex2(sg1 - a1);
            sg0 = a0; sg1 = a1; l_hi = -1.f;
            u0 = b0 * al0; u1 = b1 * al1;
#pragma unroll 1
            for (int i = 0; i < 16; i++) {
                const uint4 v = ld(st + i * 256);
                const float e0 = ex2(__uint_as_float(v.x) - a0), e1 = ex2(__uint_as_float(v.y) - a0);
                const float e2 = ex2(__uint_as_float(v.z) - a1), e3 = ex2(__uint_as_float(v.w) - a1);
                u0 += e0 + e1; u1 += e2 + e3;
                asm volatile("st.global.v2.u32 [%0], {%1, %2};" ::"l"((uint2*)(st + (i >> 1) * 256) + (i & 1)), "r"(pack_bf16(e0, e1)), "r"(pack_bf16(e2, e3)) : "memory");
            }
#pragma unroll
            for (int i = 0; i < 8; i++) {
                const uint4 v = ld(st + i * 256);
                p[4 * i] = v.x; p[4 * i + 1] = v.y; p[4 * i + 2] = v.z; p[4 * i + 3] = v.w;
            }
            if (&s != &o) {
#pragma unroll
                for (int i = 0; i < 64; i++) o[i] *= (i & 2) ? al1 : al0;
            }
        };
        auto inv_sums = [&](float& i0, float& i1) {
            float a = l0, b = l1;
            a += __shfl_xor_sync(0xffffffffu, a, 1); b += __shfl_xor_sync(0xffffffffu, b, 1);
            a += __shfl_xor_sync(0xffffffffu, a, 2); b += __shfl_xor_sync(0xffffffffu, b, 2);
            i0 = rcp(a); i1 = rcp(b);
        };

        {
            bar_sync(my_bar);
            wg_fence();
            mma_tile<0>(o, q, ring16, 0);
            mbar_wait(full + 8, 0);
            wg_fence();
            mma_tile<0>(s, q, ring16 + T16, 0);
            bar_arrive(other_bar);
            wg_wait<1>();
            TA(20);
            release_at<0>(rel);
            pin(o);
            l0 = 0.f; l1 = 0.f;
            exp_range(o, 0, 64, l0, l1);
            mbar_wait(full + 16, 1);
            wg_wait<0>();
            if (RARE(unsafe(true, l0, l1))) softmax_true_max(o, true, 0.f, 0.f, l0, l1);
        }
        uint32_t qsrc = my_stash;
        float il0 = 0.f, il1 = 0.f;
        auto step = [&](auto odd_c, int m) {
            constexpr int ODD = decltype(odd_c)::value;
            constexpr int KS = ODD ? 3 : 1, VS = ODD ? 0 : 2;
            [[maybe_unused]] const int it = 2 * m + ODD;
            const uint32_t ph = m & 1;
            TC(0);
            bar_sync(my_bar);
            TC(1);
            if (ODD || m) {
                wg_fence();
                mma_tile<0>(s, q, ring16 + KS * T16, 0);
            }
            TC(2);
            if (!ODD) {
                if ((m & 7) == 0 && m) {
#pragma unroll
                    for (int i = FSPLIT; i < 8; i++)
                        sts128(qsrc + i * 512,
                               pack_bf16(o[8 * i] * il0, o[8 * i + 1] * il0), pack_bf16(o[8 * i + 2] * il1, o[8 * i + 3] * il1),
                               pack_bf16(o[8 * i + 4] * il0, o[8 * i + 5] * il0), pack_bf16(o[8 * i + 6] * il1, o[8 * i + 7] * il1));
                    qsrc += m == 24 ? -2 * TILE_BYTES : TILE_BYTES;
                }
                wg_fence();
            }
#pragma unroll
            for (int ks = 0; ks < 8; ks++) {
                wgmma_rs<1>(o, p[4 * ks], p[4 * ks + 1], p[4 * ks + 2], p[4 * ks + 3], desc_nmajor(ring16 + VS * T16, ks),
                            (ks == 0 && !ODD) ? ((m & 7) != 0) : 1);
                if (ks == SPLIT / 8 - 1 || ks == 7) wg_commit();
            }
            TC(3);
            bar_arrive(other_bar);
            const bool last = ODD && (m & 7) == 7;
            if (last) {
                inv_sums(il0, il1);
                l0 = 0.f; l1 = 0.f; sg0 = 0.f; sg1 = 0.f; l_hi = L_HI;
            }
            wg_wait<1>();
            TA(21 + it);
            TC(4);
            release_at<8 * KS>(rel);
            const bool newq = (m & 7) == 7;
            if (!ODD) {
                lds128_if<0>(newq, qsrc, q[0], q[1], q[2], q[3]);
                lds128_if<512>(newq, qsrc, q[4], q[5], q[6], q[7]);
                lds128_if<1024>(newq, qsrc, q[8], q[9], q[10], q[11]);
            }
            pin(s);
            float u0 = l0, u1 = l1;
            exp_range(s, 0, SPLIT, u0, u1);
            mbar_wait(full + 8 * (KS ^ 2), ph ^ 1);
            if (!ODD) {
                lds128_if<1536>(newq, qsrc, q[12], q[13], q[14], q[15]);
                lds128_if<2048>(newq, qsrc, q[16], q[17], q[18], q[19]);
            }
            TC(5);
            wg_wait<0>();
            release_at<8 * VS>(rel);
            pin(o);
            exp_range(s, SPLIT, 64, u0, u1);
            TC(6);
            mbar_wait(full + 8 * (VS ^ 2), ODD ? ph : ph ^ 1);
            if (!ODD) {
                lds128_if<2560>(newq, qsrc, q[20], q[21], q[22], q[23]);
                lds128_if<3072>(newq, qsrc, q[24], q[25], q[26], q[27]);
                lds128_if<3584>(newq, qsrc, q[28], q[29], q[30], q[31]);
            } else if (last) {
#pragma unroll
                for (int i = 0; i < FSPLIT; i++)
                    sts128(qsrc + i * 512,
                           pack_bf16(o[8 * i] * il0, o[8 * i + 1] * il0), pack_bf16(o[8 * i + 2] * il1, o[8 * i + 3] * il1),
                           pack_bf16(o[8 * i + 4] * il0, o[8 * i + 5] * il0), pack_bf16(o[8 * i + 6] * il1, o[8 * i + 7] * il1));
            }
            if (RARE(unsafe(last, u0, u1))) softmax_true_max(s, last, l0, l1, u0, u1);
            l0 = u0; l1 = u1;
            TC(7);
            TF(3 + it);
        };
#pragma unroll 1
        for (int m = 0;; m++) {
            step(cint<0>(), m);
            if (m == 31) break;
            step(cint<1>(), m);
        }
        uint32_t ob[64];
        const uint32_t t128 = threadIdx.x & 127;
        uint32_t ep, tag;
        const uint32_t half = 0x8000u;
        auto send = [&](uint4* dst, const float* a) {
            asm volatile("st.relaxed.gpu.global.v4.u32 [%0], {%1, %2, %3, %4};" ::"l"(dst), "r"(lop3<0xD8>(pack_bf16(a[0], a[1]), tag, 0x10000u)),
                         "r"(pack_bf16(a[2], a[3])), "r"(pack_bf16(a[4], a[5])), "r"(pack_bf16(a[6], a[7])) : "memory");
        };
        auto hint = [&](int dst, int job) {
            asm volatile("st.relaxed.gpu.global.u32 [%0], %1;" ::"l"((uint32_t*)(sc->flag + (qt * 8 + dst) * 32 + job) + (warp & 3)), "r"(ep) : "memory");
        };
        float a32[32], own[32];
        auto half_mma = [&](const uint32_t* a, const uint32_t* b, uint32_t t16, int accumulate) {
            wg_fence();
#pragma unroll
            for (int ks = 0; ks < 8; ks++) wgmma_rs64(a32, a[4 * ks], a[4 * ks + 1], a[4 * ks + 2], a[4 * ks + 3], desc_nmajor(t16, ks), ks ? 1 : accumulate);
#pragma unroll
            for (int ks = 0; ks < 8; ks++) wgmma_rs64(a32, b[4 * ks], b[4 * ks + 1], b[4 * ks + 2], b[4 * ks + 3], desc_nmajor(t16, 8 + ks), 1);
            wg_commit();
        };
        auto block_mma = [&](uint32_t sb, uint32_t ph, bool pass_turn) {
            mbar_wait(full + 8 * sb, ph);
            bar_sync(my_bar);
            half_mma(q, ob, ring16 + sb * T16, zero);
            mbar_wait(full + 8 * sb + 8, ph);
            half_mma(ob + 32, p, ring16 + (sb + 1) * T16, 1);
            if (pass_turn) bar_arrive(other_bar);
        };
        auto send_strips = [&](int u) {
            const uint32_t t = opaque(t128);
            const int d0 = (grp & 4) ^ (4 * u);
            uint4* dst = sc->part + (((qt * 8 + d0) * 9 + u) * 2 + wg) * 512 + (grp & 3) * 128 + t;
#pragma unroll
            for (int i = 0; i < 4; i++) send(dst + i * 9 * 1024, a32 + 8 * i);
            if ((t & 31) < 4) hint(d0 + (t & 31), u * 8 + (grp & 3) * 2 + wg);
        };
        uint32_t xs[4], gs[4];
        {
            [[maybe_unused]] const int c = 9;
            TS(0);
            auto fetch_o = [&](int lo, int hi) {
#pragma unroll
                for (int i = lo; i < hi; i++)
                    lds128(qsrc + (1 + (i >> 3)) * TILE_BYTES + (i & 7) * 512, ob[4 * i], ob[4 * i + 1], ob[4 * i + 2], ob[4 * i + 3]);
            };
            fetch_o(0, 3);
            bar_sync(my_bar);
            wg_fence();
            mma_tile<1>(o, p, ring16 + 3 * T16, 1);
            sched_fence(zero);
            inv_sums(il0, il1);
            asm volatile("" : "+f"(il0), "+f"(il1));
            sched_fence(zero);
            fetch_o(3, 6);
            wg_fence();
#pragma unroll
            for (int ks = 0; ks < 8; ks++) {
                wgmma_rs64(a32, q[4 * ks], q[4 * ks + 1], q[4 * ks + 2], q[4 * ks + 3], desc_nmajor(ring16, ks), ks);
                if (ks == 3) { wg_commit(); sched_fence(zero); fetch_o(6, 8); wg_fence(); }
            }
            TS(1);
#pragma unroll
            for (int ks = 0; ks < 8; ks++) wgmma_rs64(a32, ob[4 * ks], ob[4 * ks + 1], ob[4 * ks + 2], ob[4 * ks + 3], desc_nmajor(ring16, 8 + ks), 1);
            wg_commit();
            TS(2);
            bar_arrive(other_bar);
            wg_wait<1>();
            release_at<24>(rel);
            pin(o);
#pragma unroll
            for (int i = 0; i < 32; i++) {
                const float r = (i & 1) ? il1 : il0;
                asm volatile("cvt.rn.bf16x2.f32 %0, %1, %2;" : "=r"(p[i]) : "f"(o[2 * i + 1] * r), "f"(o[2 * i] * r));
                if ((i & 7) == 7) fetch_o(8 + (i >> 3) * 2, 10 + (i >> 3) * 2);
            }
            TS(3);
            mbar_wait(full + 8, 0);
            wg_wait<0>();
            release_at<0>(rel);
            __syncwarp();
            if (lane == 0) mbar_arrive(vacant);
            TS(4);
            bar_sync(my_bar);
            half_mma(ob + 32, p, ring16 + T16, 1);
            TS(5);
            bar_arrive(other_bar);
            TR(66);
            TG(113);
            mbar_wait(routed, 0);
            asm volatile("ld.shared.u32 %0, [%1];" : "=r"(ep) : "r"(epoch));
            tag = ep << 16;
            const uint4* src = sc->gate + (blockIdx.x * 5 + 4) * 512 + threadIdx.x;
            asm volatile("ld.global.cg.v4.u32 {%0, %1, %2, %3}, [%4];" : "=r"(xs[0]), "=r"(xs[1]), "=r"(xs[2]), "=r"(xs[3]) : "l"(src));
            asm volatile("ld.global.cg.v4.u32 {%0, %1, %2, %3}, [%4];" : "=r"(gs[0]), "=r"(gs[1]), "=r"(gs[2]), "=r"(gs[3]) : "l"(src + 256));
            sched_fence(zero);
            wg_wait<0>();
            TS(6);
            release_at<8>(rel);
            pin(a32);
            send_strips(0);
            TS(7);
        }
        uint32_t v[4][4];
        auto stale = [&]() {
            return __any_sync(0xffffffffu, lop3<0xA8>(lop3<0x7E>(v[0][0], v[1][0], tag), lop3<0x7E>(v[2][0], v[3][0], tag), 0x10000u));
        };
        auto recv = [&](int u) {
            mbar_wait(rfull + 16 * u + 8 * wg, 0);
#pragma unroll
            for (int i = 0; i < 4; i++)
                lds128(stash + (u >= 6 ? u - 6 : u) * 16384 + wg * 8192 + i * 2048 + t128 * 16, v[i][0], v[i][1], v[i][2], v[i][3]);
            if (stale()) {
                const uint4* src = sc->part + (((qt * 8 + grp) * 9 + u) * 2 + wg) * 512 + opaque(t128);
                uint32_t spins = 0;
                do {
#pragma unroll
                    for (int i = 0; i < 4; i++)
                        asm volatile("ld.relaxed.gpu.global.v4.u32 {%0, %1, %2, %3}, [%4];" : "=r"(v[i][0]), "=r"(v[i][1]), "=r"(v[i][2]), "=r"(v[i][3])
                                     : "l"(src + i * 128) : "memory");
                } while (stale() && ++spins < 2000000u);
            }
            if (u < 3 && lane == 0) mbar_arrive(rdone + (u * 2 + wg) * 8);
        };
        auto accumulate = [&](float* dst, int stride) {
#pragma unroll
            for (int i = 0; i < 4; i++) {
                float* a = dst + stride * i;
                a[0] += bf_lo(v[i][0]);
                a[1] += __uint_as_float(lop3<0xEC>(v[i][0], half, 0xfffe0000u));
#pragma unroll
                for (int k = 1; k < 4; k++) { a[2 * k] += bf_lo(v[i][k]); a[2 * k + 1] += bf_hi(v[i][k]); }
            }
        };
        auto gate = [](uint32_t x2, uint32_t g2, float lo, float hi) {
            uint32_t sv = pack_bf16(lo, hi);
            asm("mul.rn.bf16x2 %0, %0, %1;" : "+r"(sv) : "r"(g2));
            asm("add.rn.bf16x2 %0, %0, %1;" : "+r"(sv) : "r"(x2));
            return sv;
        };
        uint4* const outbox = sc->part + qt * (8 * 9 * 1024) + wg * 512 + t128;
        auto step_o = [&](int f) {
            [[maybe_unused]] const int c = f;
            const uint32_t sb = (f & 1) ? 0 : 2;
            block_mma(sb, (((f + 3) >> 1) ^ f) & 1, true);
            wg_wait<1>();
            const uint32_t rl = rel && f < 7 ? rel + 8 * sb : 0;
            release_at<0>(rl);
            if (f >= 1) recv(f - 1);
            wg_wait<0>();
            TS(0);
            release_at<8>(rl);
            pin(a32);
            if (f == 0) {
                send_strips(1);
            } else {
                const int d = (grp + f) & 7;
#pragma unroll
                for (int i = 0; i < 4; i++) send(outbox + (d * 9 + f + 1) * 1024 + i * 128, a32 + 8 * i);
                if (lane == 0) hint(d, 14 + 2 * f + wg);
            }
            TS(1);
        };
        {
            float st[8] = {};
#pragma unroll 1
            for (int f = 0; f < 3; f++) {
                [[maybe_unused]] const int c = f;
                step_o(f);
                if (f >= 1) accumulate(st, 0);
                TS(2);
            }
            uint32_t w[4];
#pragma unroll
            for (int i = 0; i < 4; i++) w[i] = gate(xs[i], gs[i], st[2 * i], st[2 * i + 1]);
            const bool odd = lane & 1;
            const uint32_t r0 = __shfl_xor_sync(0xffffffffu, odd ? w[0] : w[2], 1), r1 = __shfl_xor_sync(0xffffffffu, odd ? w[1] : w[3], 1);
            uint2* dst = (uint2*)out + (qt * 128 + warp * 16 + (lane >> 2)) * (DM / 4) + 128 + grp * 4 + (lane & 1) * 2 + ((lane >> 1) & 1);
            dst[0] = odd ? make_uint2(r0, w[2]) : make_uint2(w[0], r0);
            dst[2 * DM] = odd ? make_uint2(r1, w[3]) : make_uint2(w[1], r1);
        }
#pragma unroll
        for (int i = 0; i < 32; i++) own[i] = 0.f;
#pragma unroll 1
        for (int f = 3; f < 8; f++) {
            [[maybe_unused]] const int c = f;
            step_o(f);
            accumulate(own, 8);
            TS(2);
        }
        {
            [[maybe_unused]] const int c = 8;
            block_mma(2, 1, wg == 0);
            TR(71);
            TS(0);
            recv(7);
            TS(7);
            accumulate(own, 8);
            TS(1);
            wg_wait<0>();
            pin(a32);
            uint32_t xv[16], gv[16];
            mbar_wait(xgfull, 0);
#pragma unroll
            for (int j = 0; j < 4; j++) {
                lds128(stash + 3 * 16384 + j * 8192 + threadIdx.x * 16, xv[4 * j], xv[4 * j + 1], xv[4 * j + 2], xv[4 * j + 3]);
                lds128(stash + 3 * 16384 + j * 8192 + 4096 + threadIdx.x * 16, gv[4 * j], gv[4 * j + 1], gv[4 * j + 2], gv[4 * j + 3]);
            }
#pragma unroll
            for (int i = 0; i < 32; i++) own[i] += a32[i];
            TS(2);
            recv(8);
            accumulate(own, 8);
            TS(3);
            const uint32_t tb = ring + warp * 2048;
#pragma unroll
            for (int j = 0; j < 4; j++)
                stsm4(tb + (lane & 15) * 128 + (((2 * j + (lane >> 4)) ^ (lane & 7)) << 4),
                      gate(xv[4 * j], gv[4 * j], own[8 * j], own[8 * j + 1]), gate(xv[4 * j + 1], gv[4 * j + 1], own[8 * j + 2], own[8 * j + 3]),
                      gate(xv[4 * j + 2], gv[4 * j + 2], own[8 * j + 4], own[8 * j + 5]), gate(xv[4 * j + 3], gv[4 * j + 3], own[8 * j + 6], own[8 * j + 7]));
            __syncwarp();
#pragma unroll
            for (int j = 0; j < 4; j++) {
                const uint32_t row = j * 4 + (lane >> 3);
                uint4 v;
                lds128(tb + row * 128 + (((lane & 7) ^ (row & 7)) << 4), v.x, v.y, v.z, v.w);
                ((uint4*)out)[(qt * 128 + warp * 16 + row) * (DM / 8) + grp * 8 + (lane & 7)] = v;
            }
        }
        TR(73);
        TG(111);
    }
}

typedef CUresult (*EncodeFn)(CUtensorMap*, CUtensorMapDataType, cuuint32_t, void*, const cuuint64_t*, const cuuint64_t*,
                             const cuuint32_t*, const cuuint32_t*, CUtensorMapInterleave, CUtensorMapSwizzle,
                             CUtensorMapL2promotion, CUtensorMapFloatOOBfill);

void make_map(EncodeFn enc, CUtensorMap* tm, const void* ptr, uint64_t cols, uint64_t rows) {
    cuuint64_t gd[2] = {cols, rows};
    cuuint64_t gs[1] = {cols * 2};
    cuuint32_t bd[2] = {64, 128};
    cuuint32_t es[2] = {1, 1};
    enc(tm, CU_TENSOR_MAP_DATA_TYPE_BFLOAT16, 2, const_cast<void*>(ptr), gd, gs, bd, es, CU_TENSOR_MAP_INTERLEAVE_NONE,
        CU_TENSOR_MAP_SWIZZLE_128B, CU_TENSOR_MAP_L2_PROMOTION_L2_256B, CU_TENSOR_MAP_FLOAT_OOB_FILL_NONE);
}

}

extern "C" void kernel_launch(void* const* d_in, const int* in_sizes, int n_in, void* d_out, int out_size) {
    const __nv_bfloat16* x = (const __nv_bfloat16*)d_in[0];
    const __nv_bfloat16* wr = (const __nv_bfloat16*)d_in[6];
    __nv_bfloat16* out = (__nv_bfloat16*)d_out;

    EncodeFn enc = nullptr;
    cudaDriverEntryPointQueryResult qr;
    cudaGetDriverEntryPoint("cuTensorMapEncodeTiled", (void**)&enc, cudaEnableDefault, &qr);
    CUtensorMap tm_x, tm_wq, tm_k, tm_v, tm_wo, tm_g, tm_u, tm_d;
    {
        cuuint64_t gd[3] = {64, SEQ, DM / 64};
        cuuint64_t gs[2] = {DM * 2, 128};
        cuuint32_t bd[3] = {64, 64, 2};
        cuuint32_t es[3] = {1, 1, 1};
        enc(&tm_x, CU_TENSOR_MAP_DATA_TYPE_BFLOAT16, 3, d_in[0], gd, gs, bd, es, CU_TENSOR_MAP_INTERLEAVE_NONE,
            CU_TENSOR_MAP_SWIZZLE_128B, CU_TENSOR_MAP_L2_PROMOTION_L2_256B, CU_TENSOR_MAP_FLOAT_OOB_FILL_NONE);
    }
    make_map(enc, &tm_k, d_in[1], DH, (uint64_t)NH * SEQ);
    make_map(enc, &tm_v, d_in[2], DH, (uint64_t)NH * SEQ);
    make_map(enc, &tm_wq, d_in[3], NH * DH, DM);
    make_map(enc, &tm_wo, d_in[4], DM, NH * DH);
    make_map(enc, &tm_g, d_in[7], FF, DM);
    make_map(enc, &tm_u, d_in[8], FF, DM);
    make_map(enc, &tm_d, d_in[9], DM, FF);
    cudaFuncSetAttribute(fused_attn_kernel, cudaFuncAttributeMaxDynamicSharedMemorySize, SMEM_BYTES);

    Scratch* sc = nullptr;
    cudaGetSymbolAddress((void**)&sc, g_scratch);

    cudaLaunchConfig_t cfg = {};
    cfg.gridDim = dim3(N_MAIN + N_MOE);
    cfg.blockDim = dim3(384);
    cfg.dynamicSmemBytes = SMEM_BYTES;
    cfg.stream = cudaStreamPerThread;
    cudaLaunchAttribute at[1];
    at[0].id = cudaLaunchAttributeClusterDimension;
    at[0].val.clusterDim.x = 2; at[0].val.clusterDim.y = 1; at[0].val.clusterDim.z = 1;
    cfg.attrs = at; cfg.numAttrs = 1;
    cudaLaunchKernelEx(&cfg, fused_attn_kernel, x, wr, out, sc, tm_x, tm_wq, tm_k, tm_v, tm_wo, tm_g, tm_u, tm_d);
}
```

```cpp
#include <cuda_runtime.h>
#include <cuda.h>
#include <cuda_bf16.h>
#include <stdint.h>

namespace {

constexpr int SEQ = 2048, DM = 640, NH = 32, DH = 128, FF = 1728, CAP = 8;
constexpr int NSLOT = 4;
constexpr int TILE_BYTES = 32768;
constexpr uint32_t RING_OFFSET = 1024;
constexpr int SMEM_BYTES = (NSLOT + 3) * TILE_BYTES + 416 + 1408 + 96;
constexpr int N_MAIN = 128, N_MOE = 4;

struct Scratch {
    uint4 part[16 * 8 * 9 * 2 * 4 * 128];
    uint4 gate[N_MAIN * 5 * 2 * 256];
    uint4 flag[16 * 8 * 32];
    uint4 qoff[16 * 4 * 2048];
    uint32_t flag_q[16];
    uint4 rare[N_MAIN * 17 * 256];
    float y[N_MOE * CAP * DM];
    uint2 routed[CAP * DM / 4];
    uint2 stat[SEQ];
    float r[SEQ];
    int idx[CAP];
    uint32_t flag_r[N_MOE], flag_y[N_MOE], flag_u[N_MOE];
    uint32_t epoch[N_MAIN + N_MOE];
};
__device__ Scratch g_scratch;

__device__ __forceinline__ uint32_t smem_u32(const void* p) { return (uint32_t)__cvta_generic_to_shared(p); }
__device__ __forceinline__ void mbar_init(uint32_t bar, uint32_t cnt) {
    asm volatile("mbarrier.init.shared::cta.b64 [%0], %1;" ::"r"(bar), "r"(cnt) : "memory");
}
#define HOTW 2
__device__ __forceinline__ void mbar_wait(uint32_t bar, uint32_t parity) {
    asm volatile(
        "{\n.reg .pred p;\n"
        "LOOP:\n"
        "mbarrier.try_wait.parity.shared::cta.b64 p, [%0], %1;\n"
        "@!p bra.uni LOOP;\n"
        "DONE:\n}\n" ::"r"(bar), "r"(parity) : "memory");
}
__device__ __forceinline__ void mbar_wait_hot(uint32_t bar, uint32_t parity) {
    asm volatile(
        "{\n.reg .pred p;\n.reg .u32 c;\n"
        "mbarrier.test_wait.parity.shared::cta.b64 p, [%0], %1;\n"
        "@p bra.uni DONE;\n"
        "mov.u32 c, 0;\n"
        "LOOP:\n"
        "mbarrier.try_wait.parity.shared::cta.b64 p, [%0], %1;\n"
        "@p bra.uni DONE;\n"
        "add.u32 c, c, 1;\n"
        "setp.lt.u32 p, c, 2000000;\n"
        "@p bra.uni LOOP;\n"
        "trap;\n"
        "DONE:\n}\n" ::"r"(bar), "r"(parity) : "memory");
}
__device__ __forceinline__ void mbar_wait_bounded(uint32_t bar, uint32_t parity) {
    asm volatile(
        "{\n.reg .pred p;\n.reg .u32 c;\n"
        "mov.u32 c, 0;\n"
        "LOOP:\n"
        "mbarrier.try_wait.parity.shared::cta.b64 p, [%0], %1;\n"
        "@p bra.uni DONE;\n"
        "add.u32 c, c, 1;\n"
        "setp.lt.u32 p, c, 2000000;\n"
        "@p bra.uni LOOP;\n"
        "trap;\n"
        "DONE:\n}\n" ::"r"(bar), "r"(parity) : "memory");
}
__device__ __forceinline__ void mbar_wait_sleep(uint32_t bar, uint32_t parity) {
    asm volatile(
        "{\n.reg .pred p;\n.reg .u32 c;\n"
        "mov.u32 c, 0;\n"
        "LOOP:\n"
        "mbarrier.test_wait.parity.shared::cta.b64 p, [%0], %1;\n"
        "@p bra.uni DONE;\n"
        "nanosleep.u32 500;\n"
        "add.u32 c, c, 1;\n"
        "setp.lt.u32 p, c, 1000000;\n"
        "@p bra.uni LOOP;\n"
        "trap;\n"
        "DONE:\n}\n" ::"r"(bar), "r"(parity) : "memory");
}
__device__ __forceinline__ void mbar_expect_tx(uint32_t bar, uint32_t bytes) {
    asm volatile("mbarrier.arrive.expect_tx.shared::cta.b64 _, [%0], %1;" ::"r"(bar), "r"(bytes) : "memory");
}
template <int OFF>
__device__ __forceinline__ void release_at(uint32_t bar) {
    asm volatile(
        "{\n.reg .pred p;\n"
        "setp.ne.u32 p, %0, 0;\n"
        "@p mbarrier.arrive.shared::cluster.b64 _, [%0 + %1];\n}\n" ::"r"(bar), "n"(OFF) : "memory");
}
__device__ __forceinline__ void sched_fence(int zero) {
    asm volatile("{\n.reg .pred p;\n.reg .u32 c;\nsetp.ne.s32 p, %0, 0;\n@p mov.u32 c, %%clock;\n@p st.shared.u32 [%0], c;\n}\n" ::"r"(zero) : "memory");
}
__device__ __forceinline__ bool elect_one() {
    uint32_t r;
    asm volatile("{\n.reg .pred p;\nelect.sync _|p, 0xffffffff;\nselp.u32 %0, 1, 0, p;\n}\n" : "=r"(r));
    return r;
}
__device__ __forceinline__ uint32_t opaque(uint32_t v) {
    uint32_t r;
    asm volatile("mov.u32 %0, %1;" : "=r"(r) : "r"(v));
    return r;
}
__device__ __forceinline__ void tma_2d(uint32_t dst, const CUtensorMap* tm, uint32_t bar, int c0, int c1) {
    asm volatile(
        "cp.async.bulk.tensor.2d.shared::cluster.global.mbarrier::complete_tx::bytes [%0], [%1, {%3, %4}], [%2];"
        ::"r"(dst), "l"(tm), "r"(bar), "r"(c0), "r"(c1) : "memory");
}
__device__ __forceinline__ void tma_3d(uint32_t dst, const CUtensorMap* tm, uint32_t bar, int c0, int c1, int c2) {
    asm volatile(
        "cp.async.bulk.tensor.3d.shared::cluster.global.mbarrier::complete_tx::bytes [%0], [%1, {%3, %4, %5}], [%2];"
        ::"r"(dst), "l"(tm), "r"(bar), "r"(c0), "r"(c1), "r"(c2) : "memory");
}
__device__ __forceinline__ void tma_2d_mc(uint32_t dst, const CUtensorMap* tm, uint32_t bar, int c0, int c1) {
    asm volatile(
        "cp.async.bulk.tensor.2d.shared::cluster.global.mbarrier::complete_tx::bytes.multicast::cluster "
        "[%0], [%1, {%3, %4}], [%2], %5;"
        ::"r"(dst), "l"(tm), "r"(bar), "r"(c0), "r"(c1), "h"((uint16_t)3) : "memory");
}
__device__ __forceinline__ void tma_prefetch(const CUtensorMap* tm, int c0, int c1) {
    asm volatile("cp.async.bulk.prefetch.tensor.2d.L2.global [%0, {%1, %2}];" ::"l"(tm), "r"(c0), "r"(c1) : "memory");
}
__device__ __forceinline__ void mbar_arrive(uint32_t bar) {
    asm volatile("mbarrier.arrive.shared::cta.b64 _, [%0];" ::"r"(bar) : "memory");
}
__device__ __forceinline__ void flag_set(uint32_t* f, uint32_t v) {
    asm volatile("st.release.gpu.global.u32 [%0], %1;" ::"l"(f), "r"(v) : "memory");
}
template <int SLEEP_NS = 0>
__device__ __forceinline__ void flag_wait(const uint32_t* f, uint32_t v) {
    asm volatile(
        "{\n.reg .pred p;\n.reg .u32 c;\n"
        "LOOP:\n"
        "setp.ne.u32 p, %2, 0;\n"
        "@p nanosleep.u32 %2;\n"
        "ld.acquire.gpu.global.u32 c, [%0];\n"
        "setp.ne.u32 p, c, %1;\n"
        "@p bra LOOP;\n}\n" ::"l"(f), "r"(v), "n"(SLEEP_NS) : "memory");
}
template <int SLEEP_NS>
__device__ __forceinline__ void flag_wait_bounded(const uint32_t* f, uint32_t v) {
    asm volatile(
        "{\n.reg .pred p;\n.reg .u32 c, n;\n"
        "mov.u32 n, 0;\n"
        "LOOP:\n"
        "setp.ne.u32 p, %2, 0;\n"
        "@p nanosleep.u32 %2;\n"
        "ld.acquire.gpu.global.u32 c, [%0];\n"
        "setp.eq.u32 p, c, %1;\n"
        "@p bra DONE;\n"
        "add.u32 n, n, 1;\n"
        "setp.lt.u32 p, n, %3;\n"
        "@p bra LOOP;\n"
        "trap;\n"
        "DONE:\n}\n" ::"l"(f), "r"(v), "n"(SLEEP_NS), "n"(2000000) : "memory");
}
__device__ __forceinline__ void hmma(float (&d)[4], uint32_t a0, uint32_t a1, uint32_t a2, uint32_t a3, uint32_t b0, uint32_t b1) {
    asm volatile("mma.sync.aligned.m16n8k16.row.col.f32.bf16.bf16.f32 {%0,%1,%2,%3}, {%4,%5,%6,%7}, {%8,%9}, {%0,%1,%2,%3};"
                 : "+f"(d[0]), "+f"(d[1]), "+f"(d[2]), "+f"(d[3]) : "r"(a0), "r"(a1), "r"(a2), "r"(a3), "r"(b0), "r"(b1));
}
__device__ __forceinline__ void hmma8(float (&d)[4], uint32_t a0, uint32_t a1, uint32_t b0) {
    asm volatile("mma.sync.aligned.m16n8k8.row.col.f32.bf16.bf16.f32 {%0,%1,%2,%3}, {%4,%5}, {%6}, {%0,%1,%2,%3};"
                 : "+f"(d[0]), "+f"(d[1]), "+f"(d[2]), "+f"(d[3]) : "r"(a0), "r"(a1), "r"(b0));
}
__device__ __forceinline__ void ldsm4(uint32_t addr, uint32_t& a, uint32_t& b, uint32_t& c, uint32_t& d) {
    asm volatile("ldmatrix.sync.aligned.m8n8.x4.shared.b16 {%0, %1, %2, %3}, [%4];"
                 : "=r"(a), "=r"(b), "=r"(c), "=r"(d) : "r"(addr) : "memory");
}
__device__ __forceinline__ void stsm4(uint32_t addr, uint32_t a, uint32_t b, uint32_t c, uint32_t d) {
    asm volatile("stmatrix.sync.aligned.m8n8.x4.shared.b16 [%4], {%0, %1, %2, %3};"
                 ::"r"(a), "r"(b), "r"(c), "r"(d), "r"(addr) : "memory");
}
__device__ __forceinline__ uint32_t bf2_sub(uint32_t a, uint32_t b) {
    uint32_t d;
    asm("sub.rn.bf16x2 %0, %1, %2;" : "=r"(d) : "r"(a), "r"(b));
    return d;
}
template <int LUT>
__device__ __forceinline__ uint32_t lop3(uint32_t a, uint32_t b, uint32_t c) {
    uint32_t d;
    asm("lop3.b32 %0, %1, %2, %3, %4;" : "=r"(d) : "r"(a), "r"(b), "r"(c), "n"(LUT));
    return d;
}
__device__ __forceinline__ float rcp(float x) {
    float y;
    asm("rcp.approx.ftz.f32 %0, %1;" : "=f"(y) : "f"(x));
    return y;
}
__device__ __forceinline__ void bar_sync(int id) { asm volatile("bar.sync %0, 256;" ::"r"(id) : "memory"); }
__device__ __forceinline__ void bar_arrive(int id) { asm volatile("bar.arrive %0, 256;" ::"r"(id) : "memory"); }
__device__ __forceinline__ void wg_fence() { asm volatile("wgmma.fence.sync.aligned;" ::: "memory"); }
__device__ __forceinline__ void wg_commit() { asm volatile("wgmma.commit_group.sync.aligned;" ::: "memory"); }
template <int N> __device__ __forceinline__ void wg_wait() { asm volatile("wgmma.wait_group.sync.aligned %0;" ::"n"(N) : "memory"); }
template <int N>
__device__ __forceinline__ void pin(float (&d)[N]) {
#pragma unroll
    for (int i = 0; i < N; i++) asm volatile("" : "+f"(d[i])::"memory");
}
__device__ __forceinline__ uint32_t pack_bf16(float lo, float hi) {
    uint32_t r;
    asm("cvt.rn.bf16x2.f32 %0, %1, %2;" : "=r"(r) : "f"(hi), "f"(lo));
    return r;
}
__device__ __forceinline__ float bf_lo(uint32_t v) { return __uint_as_float(v << 16); }
__device__ __forceinline__ float bf_hi(uint32_t v) { return __uint_as_float(v & 0xffff0000u); }
__device__ __forceinline__ float bf_round(float v) { return __bfloat162float(__float2bfloat16_rn(v)); }
__device__ __forceinline__ float ex2(float x) {
    float y;
    asm("ex2.approx.ftz.f32 %0, %1;" : "=f"(y) : "f"(x));
    return y;
}
__device__ __forceinline__ void sts128(uint32_t addr, uint32_t a, uint32_t b, uint32_t c, uint32_t d) {
    asm volatile("st.shared.v4.b32 [%0], {%1, %2, %3, %4};" ::"r"(addr), "r"(a), "r"(b), "r"(c), "r"(d) : "memory");
}
__device__ __forceinline__ void lds128(uint32_t addr, uint32_t& a, uint32_t& b, uint32_t& c, uint32_t& d) {
    asm volatile("ld.shared.v4.b32 {%0, %1, %2, %3}, [%4];" : "=r"(a), "=r"(b), "=r"(c), "=r"(d) : "r"(addr) : "memory");
}

template <int OFF>
__device__ __forceinline__ void lds128_if(bool on, uint32_t addr, uint32_t& a, uint32_t& b, uint32_t& c, uint32_t& d) {
    asm volatile("{\n.reg .pred p;\nsetp.ne.u32 p, %5, 0;\n@p ld.shared.v4.b32 {%0, %1, %2, %3}, [%4 + %6];\n}\n"
                 : "+r"(a), "+r"(b), "+r"(c), "+r"(d) : "r"(addr), "r"((uint32_t)on), "n"(OFF) : "memory");
}

template <int TB>
__device__ __forceinline__ void wgmma_rs(float (&d)[64], uint32_t a0, uint32_t a1, uint32_t a2, uint32_t a3,
                                         uint64_t desc, int scale_d) {
    asm volatile(
        "{\n.reg .pred p;\nsetp.ne.b32 p, %69, 0;\n"
        "wgmma.mma_async.sync.aligned.m64n128k16.f32.bf16.bf16 "
        "{%0,%1,%2,%3,%4,%5,%6,%7,%8,%9,%10,%11,%12,%13,%14,%15,%16,%17,%18,%19,%20,%21,%22,%23,%24,%25,%26,%27,%28,%29,%30,%31,"
        "%32,%33,%34,%35,%36,%37,%38,%39,%40,%41,%42,%43,%44,%45,%46,%47,%48,%49,%50,%51,%52,%53,%54,%55,%56,%57,%58,%59,%60,%61,%62,%63},"
        "{%64,%65,%66,%67}, %68, p, 1, 1, %70;\n}\n"
        : "+f"(d[0]), "+f"(d[1]), "+f"(d[2]), "+f"(d[3]), "+f"(d[4]), "+f"(d[5]), "+f"(d[6]), "+f"(d[7]),
          "+f"(d[8]), "+f"(d[9]), "+f"(d[10]), "+f"(d[11]), "+f"(d[12]), "+f"(d[13]), "+f"(d[14]), "+f"(d[15]),
          "+f"(d[16]), "+f"(d[17]), "+f"(d[18]), "+f"(d[19]), "+f"(d[20]), "+f"(d[21]), "+f"(d[22]), "+f"(d[23]),
          "+f"(d[24]), "+f"(d[25]), "+f"(d[26]), "+f"(d[27]), "+f"(d[28]), "+f"(d[29]), "+f"(d[30]), "+f"(d[31]),
          "+f"(d[32]), "+f"(d[33]), "+f"(d[34]), "+f"(d[35]), "+f"(d[36]), "+f"(d[37]), "+f"(d[38]), "+f"(d[39]),
          "+f"(d[40]), "+f"(d[41]), "+f"(d[42]), "+f"(d[43]), "+f"(d[44]), "+f"(d[45]), "+f"(d[46]), "+f"(d[47]),
          "+f"(d[48]), "+f"(d[49]), "+f"(d[50]), "+f"(d[51]), "+f"(d[52]), "+f"(d[53]), "+f"(d[54]), "+f"(d[55]),
          "+f"(d[56]), "+f"(d[57]), "+f"(d[58]), "+f"(d[59]), "+f"(d[60]), "+f"(d[61]), "+f"(d[62]), "+f"(d[63])
        : "r"(a0), "r"(a1), "r"(a2), "r"(a3), "l"(desc), "r"(scale_d), "n"(TB));
}
__device__ __forceinline__ void wgmma_ss(float (&d)[64], uint64_t desc_a, uint64_t desc_b, int scale_d) {
    asm volatile(
        "{\n.reg .pred p;\nsetp.ne.b32 p, %66, 0;\n"
        "wgmma.mma_async.sync.aligned.m64n128k16.f32.bf16.bf16 "
        "{%0,%1,%2,%3,%4,%5,%6,%7,%8,%9,%10,%11,%12,%13,%14,%15,%16,%17,%18,%19,%20,%21,%22,%23,%24,%25,%26,%27,%28,%29,%30,%31,"
        "%32,%33,%34,%35,%36,%37,%38,%39,%40,%41,%42,%43,%44,%45,%46,%47,%48,%49,%50,%51,%52,%53,%54,%55,%56,%57,%58,%59,%60,%61,%62,%63},"
        "%64, %65, p, 1, 1, 0, 1;\n}\n"
        : "+f"(d[0]), "+f"(d[1]), "+f"(d[2]), "+f"(d[3]), "+f"(d[4]), "+f"(d[5]), "+f"(d[6]), "+f"(d[7]),
          "+f"(d[8]), "+f"(d[9]), "+f"(d[10]), "+f"(d[11]), "+f"(d[12]), "+f"(d[13]), "+f"(d[14]), "+f"(d[15]),
          "+f"(d[16]), "+f"(d[17]), "+f"(d[18]), "+f"(d[19]), "+f"(d[20]), "+f"(d[21]), "+f"(d[22]), "+f"(d[23]),
          "+f"(d[24]), "+f"(d[25]), "+f"(d[26]), "+f"(d[27]), "+f"(d[28]), "+f"(d[29]), "+f"(d[30]), "+f"(d[31]),
          "+f"(d[32]), "+f"(d[33]), "+f"(d[34]), "+f"(d[35]), "+f"(d[36]), "+f"(d[37]), "+f"(d[38]), "+f"(d[39]),
          "+f"(d[40]), "+f"(d[41]), "+f"(d[42]), "+f"(d[43]), "+f"(d[44]), "+f"(d[45]), "+f"(d[46]), "+f"(d[47]),
          "+f"(d[48]), "+f"(d[49]), "+f"(d[50]), "+f"(d[51]), "+f"(d[52]), "+f"(d[53]), "+f"(d[54]), "+f"(d[55]),
          "+f"(d[56]), "+f"(d[57]), "+f"(d[58]), "+f"(d[59]), "+f"(d[60]), "+f"(d[61]), "+f"(d[62]), "+f"(d[63])
        : "l"(desc_a), "l"(desc_b), "r"(scale_d));
}
__device__ __forceinline__ void wgmma_rs64(float (&d)[32], uint32_t a0, uint32_t a1, uint32_t a2, uint32_t a3,
                                           uint64_t desc, int scale_d) {
    asm volatile(
        "{\n.reg .pred p;\nsetp.ne.b32 p, %37, 0;\n"
        "wgmma.mma_async.sync.aligned.m64n64k16.f32.bf16.bf16 "
        "{%0,%1,%2,%3,%4,%5,%6,%7,%8,%9,%10,%11,%12,%13,%14,%15,%16,%17,%18,%19,%20,%21,%22,%23,%24,%25,%26,%27,%28,%29,%30,%31},"
        "{%32,%33,%34,%35}, %36, p, 1, 1, 1;\n}\n"
        : "+f"(d[0]), "+f"(d[1]), "+f"(d[2]), "+f"(d[3]), "+f"(d[4]), "+f"(d[5]), "+f"(d[6]), "+f"(d[7]),
          "+f"(d[8]), "+f"(d[9]), "+f"(d[10]), "+f"(d[11]), "+f"(d[12]), "+f"(d[13]), "+f"(d[14]), "+f"(d[15]),
          "+f"(d[16]), "+f"(d[17]), "+f"(d[18]), "+f"(d[19]), "+f"(d[20]), "+f"(d[21]), "+f"(d[22]), "+f"(d[23]),
          "+f"(d[24]), "+f"(d[25]), "+f"(d[26]), "+f"(d[27]), "+f"(d[28]), "+f"(d[29]), "+f"(d[30]), "+f"(d[31])
        : "r"(a0), "r"(a1), "r"(a2), "r"(a3), "l"(desc), "r"(scale_d));
}
__device__ __forceinline__ void wgmma_ss64(float (&d)[32], uint64_t desc_a, uint64_t desc_b, int scale_d) {
    asm volatile(
        "{\n.reg .pred p;\nsetp.ne.b32 p, %34, 0;\n"
        "wgmma.mma_async.sync.aligned.m64n64k16.f32.bf16.bf16 "
        "{%0,%1,%2,%3,%4,%5,%6,%7,%8,%9,%10,%11,%12,%13,%14,%15,%16,%17,%18,%19,%20,%21,%22,%23,%24,%25,%26,%27,%28,%29,%30,%31},"
        "%32, %33, p, 1, 1, 0, 1;\n}\n"
        : "+f"(d[0]), "+f"(d[1]), "+f"(d[2]), "+f"(d[3]), "+f"(d[4]), "+f"(d[5]), "+f"(d[6]), "+f"(d[7]),
          "+f"(d[8]), "+f"(d[9]), "+f"(d[10]), "+f"(d[11]), "+f"(d[12]), "+f"(d[13]), "+f"(d[14]), "+f"(d[15]),
          "+f"(d[16]), "+f"(d[17]), "+f"(d[18]), "+f"(d[19]), "+f"(d[20]), "+f"(d[21]), "+f"(d[22]), "+f"(d[23]),
          "+f"(d[24]), "+f"(d[25]), "+f"(d[26]), "+f"(d[27]), "+f"(d[28]), "+f"(d[29]), "+f"(d[30]), "+f"(d[31])
        : "l"(desc_a), "l"(desc_b), "r"(scale_d));
}
__device__ __forceinline__ uint64_t desc_kmajor(uint32_t tile16, int ks) {
    uint32_t lo = tile16 + ((ks >> 2) * 1024 + (ks & 3) * 2 + (1u << 16));
    return ((uint64_t)0x40000040u << 32) | lo;
}
__device__ __forceinline__ uint64_t desc_nmajor(uint32_t tile16, int ks) {
    uint32_t lo = tile16 + (ks * 128 + (1024u << 16));
    return ((uint64_t)0x40000040u << 32) | lo;
}
template <int TB>
__device__ __forceinline__ void mma_tile(float (&d)[64], const uint32_t* a, uint32_t tile16, int accumulate) {
#pragma unroll
    for (int ks = 0; ks < 8; ks++)
        wgmma_rs<TB>(d, a[4 * ks], a[4 * ks + 1], a[4 * ks + 2], a[4 * ks + 3],
                     TB ? desc_nmajor(tile16, ks) : desc_kmajor(tile16, ks), ks == 0 ? accumulate : 1);
    wg_commit();
}

#define RARE(x) (x)
template <int V> struct cint { static constexpr int value = V; };
#define GPF 126
#define XN 2
#define FINK 0
#define TAILV 1
#define QAT 110
#define FSPLIT 4
#define SPLIT 16

#define TR(i)
#define TG(i)
#define PT(k)
#define TS(k)
#define TA(k)
#define TL(k)
#define TF(i)
#define TH(w, i)
#define TC(k)

__device__ __forceinline__ float silu_f(float v) { return v * rcp(1.f + ex2(v * -1.4426950408889634f)); }

__device__ __forceinline__ float inv_den(float var) {
    float r;
    asm("sqrt.approx.f32 %0, %1;" : "=f"(r) : "f"(bf_round(bf_round(var) + 1e-5f)));
    return rcp(bf_round(r));
}
__device__ __forceinline__ uint32_t normalise(uint32_t x2, uint32_t mm, float id) {
    const uint32_t d = bf2_sub(x2, mm);
    return pack_bf16(bf_lo(d) * id, bf_hi(d) * id);
}

__device__ __forceinline__ uint32_t silu2(uint32_t u) { return pack_bf16(silu_f(bf_lo(u)), silu_f(bf_hi(u))); }

__device__ __forceinline__ uint32_t silu2_ln(uint32_t u) {
    const float a = bf_lo(u), b = bf_hi(u);
    const float da = 1.f + ex2(a * -1.4426950408889634f), db = 1.f + ex2(b * -1.4426950408889634f);
    const float r = rcp(da * db);
    return pack_bf16(a * db * r, b * da * r);
}

__device__ __forceinline__ uint2 load_stat(Scratch* sc, int row) {
    uint2 v;
    asm volatile("ld.relaxed.gpu.global.v2.u32 {%0, %1}, [%2];" : "=r"(v.x), "=r"(v.y) : "l"(sc->stat + row) : "memory");
    return make_uint2(__byte_perm(v.x, 0, 0x1010), v.y);
}

constexpr int FSLOT = 6;
__device__ __forceinline__ void ffn_role(Scratch* sc, uint32_t ring, uint32_t ffull, uint32_t fempty, uint32_t alldone, int e, uint32_t ep, int warp,
                                         const __nv_bfloat16* __restrict__ x) {
    const uint32_t xs = ring + FSLOT * TILE_BYTES, hs = xs + 10 * 1024, cand = hs + 8 * 1024, sig = cand + 256;
    int tid;
    asm volatile("mov.u32 %0, %%tid.x;" : "=r"(tid));
    const int lane = tid & 31;
    [[maybe_unused]] const int wg = warp >> 2;
    const int nb = e == N_MOE - 1 ? 6 : 7, nkt = (nb + 1) >> 1;
    auto sync = [] { asm volatile("bar.sync 3, 256;" ::: "memory"); };
    if (tid < N_MOE) flag_wait(sc->flag_r + tid, ep);
    sync();
    TR(6);

    {
        uint32_t key[8];
#pragma unroll
        for (int i = 0; i < 8; i++) {
            const int j = warp * 256 + i * 32 + lane;
            const uint32_t u = __float_as_uint(__ldcg(sc->r + j) + 0.f);
            key[i] = (((u & 0x80000000u) ? ~u : (u | 0x80000000u)) & 0xffff0000u) | (uint32_t)(SEQ - j);
        }
#pragma unroll 1
        for (int k = 0; k < CAP; k++) {
            uint32_t b = key[0];
#pragma unroll
            for (int i = 1; i < 8; i++) b = max(b, key[i]);
            b = __reduce_max_sync(0xffffffffu, b);
#pragma unroll
            for (int i = 0; i < 8; i++) if (key[i] == b) key[i] = 0;
            if (lane == 0) asm volatile("st.shared.u32 [%0], %1;" ::"r"(cand + (warp * 8 + k) * 4), "r"(b) : "memory");
        }
    }
    sync();
    {
        uint32_t k0, k1, b = 0;
        asm volatile("ld.shared.v2.u32 {%0, %1}, [%2];" : "=r"(k0), "=r"(k1) : "r"(cand + lane * 8));
#pragma unroll 1
        for (int k = 0; k <= warp; k++) {
            b = __reduce_max_sync(0xffffffffu, max(k0, k1));
            if (k0 == b) k0 = 0;
            if (k1 == b) k1 = 0;
        }
        const int row = SEQ - (int)(b & 0xffffu);
        const uint2 st = load_stat(sc, row);
        uint4 v[3];
#pragma unroll
        for (int k = 0; k < 3; k++) v[k] = __ldg((const uint4*)(x + (size_t)row * DM) + min(lane + 32 * k, DM / 8 - 1));
#pragma unroll
        for (int k = 0; k < 3; k++) {
            const int i = lane + 32 * k;
            const float id = __uint_as_float(st.y);
            if (i < DM / 8)
                sts128(xs + (i >> 3) * 1024 + warp * 128 + (((i & 7) ^ warp) << 4), normalise(v[k].x, st.x, id), normalise(v[k].y, st.x, id),
                       normalise(v[k].z, st.x, id), normalise(v[k].w, st.x, id));
        }
        asm volatile("fence.proxy.async.shared::cta;" ::: "memory");
        if (lane == 0) {
            const float sg = bf_round(rcp(1.f + __expf(-__ldcg(sc->r + row))));
            asm volatile("st.shared.v2.b32 [%0], {%1, %2};" ::"r"(sig + warp * 8), "f"(sg), "r"(row) : "memory");
        }
    }
    sync();
    TR(7);

    {
        float acc[64];
        const int g = lane >> 2, t4 = lane & 3;
        auto block = [&](uint32_t a, uint32_t n, int step, int halves) {
#pragma unroll 1
            for (int i = 0; i < halves; i += 2, n += step) {
                const uint32_t s = n % FSLOT;
                mbar_wait(ffull + 8 * s, (n / FSLOT) & 1);
                const uint32_t a16 = (((a + i * 1024) & 0x3FFFFu) >> 4) | (1u << 16);
                const uint32_t b16 = ((ring + s * TILE_BYTES) & 0x3FFFFu) >> 4;
                auto mmas = [&](auto n_c) {
                    wg_fence();
#pragma unroll
                    for (int ks = 0; ks < decltype(n_c)::value; ks++)
                        wgmma_ss(acc, ((uint64_t)0x40000000u << 32) | (a16 + (ks >> 2) * 64 + (ks & 3) * 2), desc_nmajor(b16, ks), ks || i);
                    wg_commit();
                    wg_wait<0>();
                };
                if (i + 1 < halves) mmas(cint<8>());
                else mmas(cint<4>());
                if (lane == 0) mbar_arrive(fempty + 8 * s);
            }
            pin(acc);
        };
#pragma unroll 1
        for (int o = warp >> 2; o < nb; o += 2) {
            const bool pair = (o | 1) < nb;
            block(xs, 5 * (o & ~1) + (pair ? o & 1 : 0), pair ? 2 : 1, 10);
#pragma unroll
            for (int j = 0; j < 8; j++) {
                uint32_t h = pack_bf16(silu_f(bf_round(acc[4 * j])), silu_f(bf_round(acc[4 * j + 1])));
                asm("mul.rn.bf16x2 %0, %0, %1;" : "+r"(h) : "r"(pack_bf16(acc[32 + 4 * j], acc[33 + 4 * j])));
                asm volatile("st.shared.u32 [%0], %1;" ::"r"(hs + o * 1024 + g * 128 + ((j ^ g) << 4) + t4 * 4), "r"(h) : "memory");
            }
        }
        asm volatile("fence.proxy.async.shared::cta;" ::: "memory");
        sync();
        TR(8);
#pragma unroll 1
        for (int o = warp >> 2; o < 5; o += 2) {
            block(hs, 5 * nb + (o & ~1) * nkt + (o & 1), o < 4 ? 2 : 1, nb);
            if ((warp & 3) == 0) {
#pragma unroll
                for (int j = 0; j < 16; j++)
                    *(float2*)(sc->y + (e * CAP + g) * DM + o * 128 + j * 8 + t4 * 2) = make_float2(acc[4 * j], acc[4 * j + 1]);
            }
        }
    }
    sync();
    TR(9);
    if (tid == 0) flag_set(sc->flag_y + e, ep);
    if (tid < N_MOE) flag_wait(sc->flag_y + tid, ep);
    sync();
    if (lane == 0) mbar_arrive(alldone);
#pragma unroll 1
    for (int t = tid; t < 320; t += 256) {
        const int i = 2 * e * DM + t * 4;
        float4 y = __ldcg((const float4*)(sc->y + i));
#pragma unroll
        for (int j = 1; j < N_MOE; j++) {
            const float4 z = __ldcg((const float4*)(sc->y + j * CAP * DM + i));
            y.x += z.x; y.y += z.y; y.z += z.z; y.w += z.w;
        }
        float sg;
        int row;
        asm volatile("ld.shared.v2.b32 {%0, %1}, [%2];" : "=f"(sg), "=r"(row) : "r"(sig + (i / DM) * 8));
        const int o4 = (row * DM + i % DM) / 4;
        const uint2 v = __ldg((const uint2*)x + o4), st = load_stat(sc, row);
        uint32_t u0 = normalise(v.x, st.x, __uint_as_float(st.y)), u1 = normalise(v.y, st.x, __uint_as_float(st.y));
        asm("add.rn.bf16x2 %0, %0, %1;" : "+r"(u0) : "r"(pack_bf16(bf_round(y.x) * sg, bf_round(y.y) * sg)));
        asm("add.rn.bf16x2 %0, %0, %1;" : "+r"(u1) : "r"(pack_bf16(bf_round(y.z) * sg, bf_round(y.w) * sg)));
        sc->routed[i / 4] = make_uint2(silu2(u0), silu2(u1));
        if (i % DM == 0) sc->idx[i / DM] = row;
    }
    sync();
    TR(10);
    if (tid == 0) flag_set(sc->flag_u + e, ep);
}

__global__ void __launch_bounds__(384, 1)
fused_attn_kernel(const __nv_bfloat16* __restrict__ x, const __nv_bfloat16* __restrict__ wr,
                  __nv_bfloat16* __restrict__ out, Scratch* sc,
                  const __grid_constant__ CUtensorMap tm_x, const __grid_constant__ CUtensorMap tm_wq,
                  const __grid_constant__ CUtensorMap tm_k, const __grid_constant__ CUtensorMap tm_v,
                  const __grid_constant__ CUtensorMap tm_wo, const __grid_constant__ CUtensorMap tm_g,
                  const __grid_constant__ CUtensorMap tm_u, const __grid_constant__ CUtensorMap tm_d) {
    PT(0);
    extern __shared__ __align__(16) uint8_t smem_raw[];
    const uint32_t ring = smem_u32(smem_raw);
    const uint32_t stash = ring + NSLOT * TILE_BYTES;
    const uint32_t bars = stash + 3 * TILE_BYTES;
    const uint32_t full = bars, empty = bars + 32;
    const uint32_t xfull = bars + 64;
    const uint32_t rfull = bars + 144;
    const uint32_t rdone = bars + 288;
    const uint32_t vacant = bars + 336, routed = bars + 344, xgfull = bars + 352, gated = bars + 360;
    const uint32_t soon = bars + 376, qfull = bars + 384, epv = bars + 392, alldone = bars + 400;
    const uint32_t epoch = bars + 368;
    [[maybe_unused]] const uint32_t trbuf = bars + 416;
    const uint32_t ffull = rfull, fempty = rfull + 8 * FSLOT, qdone = rdone, h1done = rdone + 32, wperm = trbuf;

    const int warp = __shfl_sync(0xffffffffu, threadIdx.x >> 5, 0), wg = warp >> 2;
    const int rank = blockIdx.x & 1;
    const int cl = blockIdx.x >> 1;
    const int r7 = ((cl - 36) * 37) >> 8;
    const int qp = cl < 36 ? (cl < 4 ? 0 : (cl - 4) & 7) : cl - 35 - 7 * r7;
    const int grp = cl < 4 ? cl + 4 : cl < 36 ? (cl - 4) >> 3 : r7 + 4;
    const bool helper = blockIdx.x >= N_MAIN;
    const int qt = helper ? (blockIdx.x - N_MAIN) * 4 : qp * 2 + rank;

    auto load_x = [&](int w, int i, int tile) {
        const uint32_t bar = xfull + (w * 5 + i) * 8;
        mbar_expect_tx(bar, 16384);
        tma_3d(ring + (i == 4 ? 2 : 3 + i) * TILE_BYTES + w * 16384, &tm_x, bar, 0, tile * 128 + w * 64, i == 0 ? 8 : 2 * i - 2);
    };
    if (warp == 4) {
        if (elect_one()) {
#pragma unroll
            for (int i = 0; i < 10; i++) mbar_init(xfull + 8 * i, 1);
#pragma unroll
            for (int i = 0; i < XN; i++) load_x(i & 1, i >> 1, qt);
            asm volatile("fence.mbarrier_init.release.cluster;" ::: "memory");
        }
        __syncwarp();
    }
    PT(6);
    if ((ring & 0xFFFFFFu) != RING_OFFSET) return;
    PT(7);
    if (warp >= 5 && elect_one()) {
        if (warp == 5) {
#pragma unroll
            for (int i = 0; i < NSLOT; i++) { mbar_init(full + 8 * i, 1); mbar_init(empty + 8 * i, 16); }
        } else if (warp == 6) {
#pragma unroll
            for (int i = 0; i < 6; i++) mbar_init(rdone + 8 * i, helper ? 8 : 4);
        } else if (warp == 7) {
            mbar_init(vacant, 8); mbar_init(routed, 32); mbar_init(xgfull, 1); mbar_init(gated, 8); mbar_init(soon, 1);
            mbar_init(qfull, 1); mbar_init(epv, 1); mbar_init(alldone, 8);
        } else if (warp == 8) {
            asm volatile("prefetch.tensormap [%0];" ::"l"(&tm_wq) : "memory");
        } else {
#pragma unroll
            for (int i = 0; i < 6; i++) mbar_init(rfull + ((warp - 9) * 6 + i) * 8, helper && warp == 10 ? 4 : 1);
        }
        asm volatile("fence.mbarrier_init.release.cluster;" ::: "memory");
    }
    __syncwarp();
    PT(1);
    asm volatile("barrier.cluster.arrive.relaxed.aligned;" ::: "memory");
    if (warp == 4) {
        if (elect_one()) {
#pragma unroll
            for (int i = XN; i < 10; i++) load_x(i & 1, i >> 1, qt);
        }
        __syncwarp();
    }

    if (wg == 2) {
        asm volatile("setmaxnreg.dec.sync.aligned.u32 24;");
        asm volatile("barrier.cluster.wait.aligned;" ::: "memory");
        uint32_t lane;
        asm volatile("mov.u32 %0, %%laneid;" : "=r"(lane));
        PT(2);
        if (warp == 8 && helper) {
          if (elect_one()) {
            mbar_arrive(full + 16);
#pragma unroll 1
            for (int t = 0; t < 4; t++) {
#pragma unroll 1
                for (int i = 0; i < 20; i++) {
                    const int s = i % 3;
                    mbar_wait(empty + 8 * s, ((t + (i + 1) / 3) & 1) ^ 1);
                    mbar_expect_tx(full + 8 * s, TILE_BYTES);
                    tma_2d_mc(ring + s * TILE_BYTES + rank * 16384, &tm_wq, full + 8 * s, (((i / 5) * 2 + rank) * 4 + 3) * 128 + 64,
                              ((i + 4) % 5) * 128);
                    if (t == 0 && i == 2) {
                        asm volatile("nanosleep.u32 1500;");
#pragma unroll 1
                        for (int k = 3 + ((blockIdx.x >> 1) & 1); k < 20; k += 2) tma_prefetch(&tm_wq, (((k / 5) * 2 + rank) * 4 + 3) * 128 + 64, ((k + 4) % 5) * 128);
                    }
                    if (i == 2 && t < 3) {
#pragma unroll 1
                        for (int k = 2; k < 8; k++) load_x(k & 1, k >> 1, qt + t + 1);
                    }
                    if (i == 18 && t < 3) {
                        mbar_wait(empty + 24, t & 1);
                        load_x(0, 0, qt + t + 1); load_x(1, 0, qt + t + 1);
                    }
                }
                if (t < 3) {
                    mbar_wait(empty + 16, t & 1);
                    mbar_arrive(full + 16);
                    load_x(0, 4, qt + t + 1); load_x(1, 4, qt + t + 1);
                }
            }
            const int e = blockIdx.x - N_MAIN, nb = e == N_MOE - 1 ? 6 : 7, nkt = (nb + 1) >> 1;
            mbar_wait(h1done, 0);
            uint32_t s = 0, ph = 1;
#pragma unroll 1
            for (int o0 = 0, w; o0 < nb + 5; o0 += w) {
                const bool up = o0 < nb;
                w = o0 + 1 < (up ? nb : nb + 5) ? 2 : 1;
#pragma unroll 1
                for (int k = 0; k < (up ? 5 : nkt) * w; k++) {
                    const int o = o0 + (k & (w - 1)), i = k >> (w - 1);
                    mbar_wait(fempty + 8 * s, ph);
                    mbar_expect_tx(ffull + 8 * s, TILE_BYTES);
                    const int c0 = up ? (e * 7 + o) * 64 : (o - nb) * 128, c1 = (up ? 0 : e * 448) + i * 128;
                    tma_2d(ring + s * TILE_BYTES, up ? &tm_g : &tm_d, ffull + 8 * s, c0, c1);
                    tma_2d(ring + s * TILE_BYTES + 16384, up ? &tm_u : &tm_d, ffull + 8 * s, up ? c0 : c0 + 64, c1);
                    if (++s == FSLOT) { s = 0; ph ^= 1; }
                }
            }
          }
        } else if (warp == 8) {
          if (elect_one()) {
            PT(3);
            mbar_arrive(full + 16);
            mbar_arrive(full + 24);
            auto coords = [&](int i, const CUtensorMap*& tm, int& c0, int& c1) {
                c0 = rank * 64;
                if (i < 20) {
                    const int ps = i / 5;
                    tm = &tm_wq; c1 = (i % 5 < 3 ? i % 5 : 7 - i % 5) * 128;
                    if (ps == 1) {
                        c0 = 0;
                        c1 = (i == 5 ? rank : i == 6 ? 2 : 4 - rank) * 128;
                    }
                    c0 += (grp * 4 + (ps < 2 ? 2 + ps : 3 - ps)) * 128;
                } else if (i < 148) {
                    const int u = i - 20;
                    const bool isk = (u == 0) || ((u & 1) && u != 127);
                    const int b = isk ? (u + 1) >> 1 : (u == 127 ? 63 : (u >> 1) - 1);
                    tm = isk ? &tm_k : &tm_v; c1 = (grp * 64 + b) * 128;
                } else {
                    tm = &tm_wo; c0 = (i < 152 ? ((i - 132) >> 1) ^ (grp >> 2) : (grp + ((i - 150) >> 1)) & 7) * 64; c1 = (grp * 4 + (i & 1) * 2 + rank) * 128;
                }
            };
#pragma unroll 1
            for (int i = 0; i < 168; i++) {
                const CUtensorMap* tm;
                int c0, c1;
                if (i == 8) i = 10;
                const int a = i < 8 ? i : i - 2;
                const int s = i < 20 ? a % 3 : (i & 3);
                const uint32_t ph = i < 20 ? ((a + 1) / 3) & 1 : ((i >> 2) & 1) ^ (s < 2);
                coords(i, tm, c0, c1);
                if (i == QAT) mbar_wait(qfull, 0);
                mbar_wait(empty + 8 * s, ph ^ 1);
                if (i == 6) {
                    mbar_expect_tx(full + 8 * s, TILE_BYTES / 2);
                    if (rank == 0) tma_2d_mc(ring + s * TILE_BYTES, tm, full + 8 * s, c0, c1);
                } else {
                    mbar_expect_tx(full + 8 * s, TILE_BYTES);
                    tma_2d_mc(ring + s * TILE_BYTES + rank * 16384, tm, full + 8 * s, c0, c1);
                }
                if (i == 140) mbar_arrive(soon);
                if (i >= 163 && i < 167) {
                    if (i == 163) {
                        TL(0);
                        mbar_wait(routed, 0);
                        asm volatile("fence.proxy.async.global;" ::: "memory");
                        TL(1);
                        mbar_expect_tx(xgfull, TILE_BYTES);
                    }
                    asm volatile("cp.async.bulk.shared::cluster.global.mbarrier::complete_tx::bytes [%0], [%1], 8192, [%2];"
                                 ::"r"(stash + 3 * 16384 + (i - 163) * 8192), "l"(sc->gate + blockIdx.x * 2560 + (i - 163) * 512), "r"(xgfull) : "memory");
                }
                if (i == 12) asm volatile("prefetch.tensormap [%0];\nprefetch.tensormap [%1];" ::"l"(&tm_k), "l"(&tm_v) : "memory");
                if (i == 140) asm volatile("prefetch.tensormap [%0];" ::"l"(&tm_wo) : "memory");
                if (i >= GPF && i < GPF + 10)
                    asm volatile("cp.async.bulk.prefetch.L2.global [%0], 4096;" ::"l"(sc->gate + blockIdx.x * 2560 + (i - GPF) * 256) : "memory");
                const int j = i < 2 ? 2 + i : i == 2 ? 4 + ((qp - 4) & 7) : i + 9;
                if (j < 168 && (j & 7) == qp && (j & ~1) != 8) {
                    coords(j, tm, c0, c1);
                    tma_prefetch(tm, c0, c1);
                }
            }
            sc->epoch[blockIdx.x] += 1;
          }
        } else if (warp == 9) {
            const uint32_t ep = sc->epoch[blockIdx.x] + 1;
            if (helper) {
#pragma unroll 1
                for (int t = 0; t < 4; t++) {
                    if (t == 3) {
                        mbar_wait_sleep(qdone + 40, 0);
                        if (lane == 0) flag_set(sc->flag_r + (blockIdx.x - N_MAIN), ep);
                    }
                    mbar_wait_sleep(qdone + 8 * t, 0);
                    if (lane == 0) flag_set(sc->flag_q + qt + t, ep);
                }
                if (lane == 0) sc->epoch[blockIdx.x] = ep;
            } else {
                mbar_wait_sleep(gated, 0);
                flag_wait_bounded<300>(sc->flag_q + qt, ep);
                asm volatile("fence.proxy.async.global;" ::: "memory");
                if (lane == 0) mbar_expect_tx(qfull, 16384);
                __syncwarp();
                if (lane < 8)
                    asm volatile("cp.async.bulk.shared::cluster.global.mbarrier::complete_tx::bytes [%0], [%1], 2048, [%2];"
                                 ::"r"(stash + 2 * TILE_BYTES + lane * 4096 + 2048),
                                   "l"(sc->qoff + ((qt * 4 + (grp >> 1)) * 8 + lane) * 256 + (grp & 1) * 128), "r"(qfull) : "memory");
            }
            mbar_wait_bounded(alldone, 0);
        } else if (helper) {
        } else if (warp == 10) {
            const uint32_t ep = sc->epoch[blockIdx.x] + 1;
            if (lane == 0) {
                asm volatile("st.shared.u32 [%0], %1;" ::"r"(epoch), "r"(ep) : "memory");
                mbar_arrive(epv);
            }
            mbar_wait_sleep(gated, 0);
            flag_wait<400>(sc->flag_u + (lane & 3), ep);
            __syncwarp();
            const int rrow = __ldcg(sc->idx + (lane & 7));
            uint32_t hit = __ballot_sync(0xffffffffu, lane < 8 && (rrow >> 7) == qt);
            while (hit) {
                const int k = __ffs(hit) - 1, row = __shfl_sync(0xffffffffu, rrow, k);
                hit &= hit - 1;
#pragma unroll 1
                for (int i = lane; i < 40; i += 32) {
                    const int th = ((row >> 4) & 7) * 32 + (row & 7) * 4 + (i & 3);
                    ((uint32_t*)sc->gate)[(((blockIdx.x * 5 + (i >> 3)) * 2 + 1) * 256 + th) * 4 + ((i >> 1) & 2) + ((row >> 3) & 1)] =
                        __ldcg((const uint32_t*)sc->routed + k * (DM / 2) + (i < 32 ? grp * 32 + i : 224 + grp * 8 + i));
                }
            }
            mbar_arrive(routed);
        } else if (warp == 11) {
            const uint32_t ep = sc->epoch[blockIdx.x] + 1;
            const uint32_t unit = lane < 16 ? lane >> 3 : (lane >> 1) - 6;
            const uint32_t ofs = (lane & 1) * 8192 + (lane < 16 ? ((lane >> 1) & 3) * 2048 : 0);
            if (lane < 18) mbar_expect_tx(rfull + 8 * lane, 8192);
            mbar_wait_sleep(soon, 0);
            uint32_t done = lane >= 30;
            do {
                if (!done) {
                    uint4 v;
                    asm volatile("ld.relaxed.gpu.global.v4.u32 {%0, %1, %2, %3}, [%4];" : "=r"(v.x), "=r"(v.y), "=r"(v.z), "=r"(v.w)
                                 : "l"(sc->flag + (qt * 8 + grp) * 32 + lane) : "memory");
                    uint32_t ok = v.x == ep && v.y == ep && v.z == ep && v.w == ep;
                    if (ok)
                        asm volatile("{\n.reg .pred p;\nmbarrier.test_wait.parity.shared::cta.b64 p, [%1], 0;\nselp.u32 %0, 1, 0, p;\n}\n"
                                     : "=r"(ok) : "r"(unit >= 6 ? rdone + (lane - 24) * 8 : vacant) : "memory");
                    done = ok;
                    if (ok)
                        asm volatile("cp.async.bulk.shared::cluster.global.mbarrier::complete_tx::bytes [%0], [%1], %2, [%3];"
                                     ::"r"(stash + (unit >= 6 ? unit - 6 : unit) * 16384 + ofs),
                                       "l"((const char*)sc->part + ((qt * 8 + grp) * 9 + unit) * 16384 + ofs), "r"(lane < 16 ? 2048 : 8192),
                                       "r"(rfull + 16 * unit + 8 * (lane & 1)) : "memory");
                }
            } while (!__all_sync(0xffffffffu, done));
        }
    } else {
        asm volatile("setmaxnreg.inc.sync.aligned.u32 240;");
        const uint32_t lane = threadIdx.x & 31;
        PT(2);
        asm volatile("barrier.cluster.wait.aligned;" ::: "memory");
        PT(3);
        const int my_bar = 1 + wg, other_bar = 2 - wg;
        const uint32_t my_stash = stash + warp * 4096 + lane * 16;
        constexpr uint32_t T16 = TILE_BYTES / 16;
        constexpr uint32_t ring16 = RING_OFFSET >> 4;
        uint32_t rel = 0;
        if (lane < 2)
            asm("mapa.shared::cluster.u32 %0, %1, %2;" : "=r"(rel) : "r"(empty), "r"(lane));
        rel = opaque(rel);

        const int zero = gridDim.y - 1;
        PT(4);

        uint32_t q[32];
        float acc[64];
        float wsum;
        uint32_t ep_tag;
        uint2 st0, st1;
        auto project = [&](auto helper_c, int job) {
            constexpr bool HELPER = decltype(helper_c)::value;
            float (&acc32)[32] = *reinterpret_cast<float (*)[32]>(&acc[0]);
            const int tile = qt + job;
            uint32_t lane = threadIdx.x & 31;
            if (HELPER) asm volatile("mov.u32 %0, %%laneid;" : "=r"(lane));
            uint32_t xa[128];
            const uint32_t lm_off = wg * 16384 + ((warp & 3) * 16 + (lane & 15)) * 128 + (((lane >> 4) ^ (lane & 7)) << 4);
            float sm[4][4] = {}, sq[4][4] = {};
            constexpr uint32_t ONES = 0x3f803f80u;
            constexpr float SC = 0.08838834764831845f * 1.4426950408889634f;
            auto squares = [&](const uint32_t* a) {
#pragma unroll
                for (int r = 0; r < 4; r++) hmma8(sq[r], a[r & 2], a[(r & 2) + 1], a[r]);
            };
            const int row = tile * 128 + warp * 16 + (lane >> 2);
            auto load_stats = [&](int t) {
                asm volatile("ld.relaxed.gpu.global.v2.u32 {%0, %1}, [%4];\nld.relaxed.gpu.global.v2.u32 {%2, %3}, [%4 + 64];"
                             : "=r"(st0.x), "=r"(st0.y), "=r"(st1.x), "=r"(st1.y) : "l"(sc->stat + t * 128 + warp * 16 + (lane >> 2)) : "memory");
            };
            uint32_t mm0, mm1;
            float rd0, rd1;
            if (HELPER && job == 0) load_stats(tile);
#pragma unroll
            for (int i = 0; i < 5; i++) {
                mbar_wait(xfull + (wg * 5 + i) * 8, HELPER ? job & 1 : 0);
                if (i == 0) PT(5);
                if (HELPER && i == 0) TR(20 + job * 8);
                if (HELPER && i == 4) TR(20 + job * 8 + 7);
                if (HELPER && job == 1) TR(110 + i);
                const uint32_t base = ring + (i == 4 ? 2 : 3 + i) * TILE_BYTES + lm_off;
                uint32_t* a = xa + (i == 0 ? 96 : 32 * (i - 1));
#pragma unroll
                for (int ks = 0; ks < 8; ks++)
                    ldsm4((base ^ ((ks & 3) << 5)) + (ks >> 2) * 8192, a[4 * ks], a[4 * ks + 1], a[4 * ks + 2], a[4 * ks + 3]);
                if (i == 4) PT(9);
                uint32_t wb[16];
#pragma unroll
                for (int ks = 0; ks < 8; ks++) {
                    wb[2 * ks] = ONES; wb[2 * ks + 1] = ONES;
                    if (HELPER)
                        asm volatile("ld.shared.v2.u32 {%0, %1}, [%2];" : "=r"(wb[2 * ks]), "=r"(wb[2 * ks + 1]) : "r"(wperm + (lane & 3) * 8 + ((i == 0 ? 32 : 8 * i - 8) + ks) * 32));
                }
#pragma unroll
                for (int ks = 0; ks < 8; ks++) {
                    hmma(sm[ks & 3], a[4 * ks], a[4 * ks + 1], a[4 * ks + 2], a[4 * ks + 3], wb[2 * ks], wb[2 * ks + 1]);
                    if (!HELPER && i < 4) squares(a + 4 * ks);
                }
                if (HELPER && i == 0) {
                    while (__any_sync(0xffffffffu, ((st0.x ^ ep_tag) | (st1.x ^ ep_tag)) >> 16)) load_stats(tile);
                    mm0 = __byte_perm(st0.x, 0, 0x1010); mm1 = __byte_perm(st1.x, 0, 0x1010);
#pragma unroll
                    for (int ks = 0; ks < 8; ks++)
                        stsm4((base ^ ((ks & 3) << 5)) + (ks >> 2) * 8192, bf2_sub(a[4 * ks], mm0), bf2_sub(a[4 * ks + 1], mm1),
                              bf2_sub(a[4 * ks + 2], mm0), bf2_sub(a[4 * ks + 3], mm1));
                    asm volatile("fence.proxy.async.shared::cta;" ::: "memory");
                }
            }
            release_at<16>(rel);
            sched_fence(zero);
            const float m0 = ((sm[0][0] + sm[1][0]) + (sm[2][0] + sm[3][0])) * (HELPER ? 1.f : 1.f / DM);
            const float m1 = ((sm[0][2] + sm[1][2]) + (sm[2][2] + sm[3][2])) * (HELPER ? 1.f : 1.f / DM);
            if (HELPER) {
                const float id0 = __uint_as_float(st0.y), id1 = __uint_as_float(st1.y);
                rd0 = SC * id0; rd1 = SC * id1;
                if ((lane & 3) == 0) {
                    sc->r[row] = bf_round((m0 - bf_lo(mm0) * wsum) * id0);
                    sc->r[row + 8] = bf_round((m1 - bf_lo(mm1) * wsum) * id1);
                }
                __syncwarp();
                if (job == 3 && lane == 0) mbar_arrive(qdone + 40);
            } else {
                mm0 = pack_bf16(m0, m0); mm1 = pack_bf16(m1, m1);
            }
            auto centre = [&](int kt) {
#pragma unroll
                for (int i = 32 * kt; i < 32 * kt + 32; i++) asm volatile("sub.rn.bf16x2 %0, %0, %1;" : "+r"(xa[i]) : "r"((i & 1) ? mm1 : mm0));
            };
            if (!HELPER) {
#pragma unroll
                for (int ks = 0; ks < 8; ks++) squares(xa + 96 + 4 * ks);
            }
            if (!HELPER) centre(0);
            if (wg == 1) bar_arrive(1);
            auto diag = [&](int r, int h) { return (lane & 4) ? sq[r][h + 1] + sq[r + 2][h + 1] : sq[r][h] + sq[r + 2][h]; };
            auto spread = [&](float v) { return __shfl_sync(0xffffffffu, v, (lane & ~3u) | (lane >> 3)) * (1.f / DM); };
            if (!HELPER) { rd0 = diag(0, 0); rd1 = diag(1, 2); }
            PT(10);

            if (HELPER) TR(20 + job * 8 + 1);
            uint32_t qs = 0, qph = HELPER ? job & 1 : 0;
            uint4 gx;
            if (HELPER) {
#pragma unroll
                for (int i = 0; i < 64; i++) acc[i] = 0.f;
            }
            const uint32_t xs16 = ring16 + 3 * T16 + wg * 1024;
            constexpr int SS = HELPER ? 0 : 3;
            auto finish_stats = [&] {
                float v0 = spread(rd0) - m0 * m0, v1 = spread(rd1) - m1 * m1;
                if (RARE(__any_sync(0xffffffffu, !(m0 * m0 <= 256.f * v0 && m1 * m1 <= 256.f * v1)))) {
                    const uint4* xr = (const uint4*)x + row * (DM / 8) + (lane & 3);
                    v0 = 0.f; v1 = 0.f;
#pragma unroll 1
                    for (int i = 0; i < DM / 32; i++) {
                        const uint4 a = __ldg(xr + 4 * i), b = __ldg(xr + DM + 4 * i);
                        const uint32_t w[8] = {a.x, a.y, a.z, a.w, b.x, b.y, b.z, b.w};
#pragma unroll
                        for (int k = 0; k < 8; k++) {
                            const uint32_t d = bf2_sub(w[k], k < 4 ? mm0 : mm1);
                            float& v = k < 4 ? v0 : v1;
                            v = fmaf(bf_lo(d), bf_lo(d), fmaf(bf_hi(d), bf_hi(d), v));
                        }
                    }
#pragma unroll
                    for (int d = 1; d <= 2; d <<= 1) { v0 += __shfl_xor_sync(0xffffffffu, v0, d); v1 += __shfl_xor_sync(0xffffffffu, v1, d); }
                    v0 *= 1.f / DM; v1 *= 1.f / DM;
                    const float e0 = m0 - bf_lo(mm0), e1 = m1 - bf_lo(mm1);
                    v0 -= e0 * e0; v1 -= e1 * e1;
                }
                const float id0 = inv_den(fmaxf(v0, 0.f)), id1 = inv_den(fmaxf(v1, 0.f));
                rd0 = SC * id0; rd1 = SC * id1;
                if (warp == grp) {
                    mbar_wait(epv, 0);
                    uint32_t tg;
                    asm volatile("ld.shared.u32 %0, [%1];" : "=r"(tg) : "r"(epoch));
                    if ((lane & 3) == 0)
                        asm volatile("st.relaxed.gpu.global.v2.u32 [%0], {%1, %2};\nst.relaxed.gpu.global.v2.u32 [%0 + 64], {%3, %4};"
                                     ::"l"(sc->stat + row), "r"(__byte_perm(mm0, tg, 0x5410)), "f"(id0), "r"(__byte_perm(mm1, tg, 0x5410)), "f"(id1) : "memory");
                }
            };
#pragma unroll 1
            for (int pass = 0;; pass++) {
                const uint32_t hs = my_stash + (pass == 2 ? 0 : pass + 1) * TILE_BYTES;
                uint4* const dst = sc->qoff + ((tile * 4 + pass) * 8 + warp) * 256 + lane;
                auto put = [&](int lo) {
#pragma unroll
                    for (int i = lo; i < lo + 4; i++) {
                        const uint4 v = make_uint4(pack_bf16(acc[8 * i] * rd0, acc[8 * i + 1] * rd0), pack_bf16(acc[8 * i + 2] * rd1, acc[8 * i + 3] * rd1),
                                                   pack_bf16(acc[8 * i + 4] * rd0, acc[8 * i + 5] * rd0), pack_bf16(acc[8 * i + 6] * rd1, acc[8 * i + 7] * rd1));
                        if (HELPER) dst[i * 32] = v;
                        else sts128(hs + i * 512, v.x, v.y, v.z, v.w);
                        if (i == 2 || i == 5) sched_fence(zero);
                    }
                };
                auto gate_load = [&](int j) {
                    const uint32_t* src = (const uint32_t*)x + (qt * 128 + warp * 16 + (lane >> 2)) * (DM / 2) + (lane & 3) +
                                          (j < 4 ? grp * 32 + j * 8 : 256 + grp * 8);
                    asm volatile("ld.global.nc.u32 %0, [%4];\nld.global.nc.u32 %1, [%4 + %5];\n"
                                 "ld.global.nc.u32 %2, [%4 + 16];\nld.global.nc.u32 %3, [%4 + %5 + 16];"
                                 : "=r"(gx.x), "=r"(gx.y), "=r"(gx.z), "=r"(gx.w) : "l"(src), "n"(8 * DM * 2));
                };
                auto gate_store = [&](int j) {
                    const float id0 = rd0 * (1.f / SC), id1 = rd1 * (1.f / SC);
                    uint4* g = sc->gate + (blockIdx.x * 5 + j) * 512 + threadIdx.x;
                    g[0] = gx;
                    g[256] = make_uint4(silu2_ln(normalise(gx.x, mm0, id0)), silu2_ln(normalise(gx.y, mm1, id1)),
                                        silu2_ln(normalise(gx.z, mm0, id0)), silu2_ln(normalise(gx.w, mm1, id1)));
                };
                auto advance = [&] {
                    const uint32_t r = rel ? rel + 8 * qs : 0;
                    if (++qs == 2) qph ^= 1;
                    if (qs == 3) qs = 0;
                    return r;
                };
                if (!HELPER && pass == 1) {
#pragma unroll
                    for (int turn = 0; turn < 3; turn++) {
                        if (turn) mbar_wait(full + 8 * qs, qph);
                        bar_sync(my_bar);
                        const uint32_t tile16 = ring16 + qs * T16;
                        wg_fence();
#pragma unroll
                        for (int ks = 0; ks < (turn == 1 ? 8 : 16); ks++) {
                            const uint32_t* a = xa + (turn == 2 ? 64 : turn * 64) + 4 * ks;
                            if (turn == 2 && ks < 8) wgmma_ss64(acc32, desc_kmajor(xs16 - (ks >> 2) * 512, ks), desc_nmajor(tile16, ks), 1);
                            else wgmma_rs64(acc32, a[0], a[1], a[2], a[3], desc_nmajor(tile16, ks), turn || ks);
                        }
                        wg_commit();
                        bar_arrive(other_bar);
                        const uint32_t rl = advance();
                        if (turn == 2) mbar_wait(full + 8 * qs, qph);
                        wg_wait<0>();
                        TA(5 + 2 * turn);
                        release_at<0>(rl);
                    }
                    pin(acc32);
                    put(0);
                    continue;
                }
                uint32_t rl = 0;
#pragma unroll
                for (int kt = 0; kt < 5; kt++) {
                    const bool takes = !HELPER || kt == 0 || kt == 2 || kt == 3, passes = !HELPER || kt == 1 || kt == 2 || kt == 4;
                    if (kt != 0 || pass == 0) mbar_wait(full + 8 * qs, qph);
                    if (takes) bar_sync(my_bar);
                    const uint32_t tile16 = ring16 + qs * T16;
                    wg_fence();
                    if (kt != SS) {
                        mma_tile<1>(acc, xa + (kt < SS ? kt : kt - 1) * 32, tile16, kt != 0);
                    } else {
#pragma unroll
                        for (int ks = 0; ks < 8; ks++) wgmma_ss(acc, desc_kmajor(xs16 - (ks >> 2) * 512, ks), desc_nmajor(tile16, ks), kt || ks);
                        wg_commit();
                    }
                    if (passes && !(HELPER && kt == 4 && pass == 3 && wg == 1)) bar_arrive(other_bar);
                    if (HELPER && pass == 0 && kt < 4) centre(kt);
                    if (!HELPER && pass == 0 && kt < 3) {
#pragma unroll
                        for (int ks = 3 * kt; ks < 3 * kt + 3 && ks < 8; ks++) {
                            const uint32_t ad = ((ring + 3 * TILE_BYTES + lm_off) ^ ((ks & 3) << 5)) + (ks >> 2) * 8192;
                            uint32_t a, b, c, d;
                            ldsm4(ad, a, b, c, d);
                            stsm4(ad, bf2_sub(a, mm0), bf2_sub(b, mm1), bf2_sub(c, mm0), bf2_sub(d, mm1));
                        }
                        if (kt == 2) asm volatile("fence.proxy.async.shared::cta;" ::: "memory");
                    }
                    if (!HELPER && pass == 0 && kt == FINK) finish_stats();
                    if (HELPER && kt == 2 && pass == 3 && job < 3) load_stats(tile + 1);
                    if (!HELPER && pass >= 2 && kt < 4) {
                        if (kt & 1) gate_store((pass - 2) * 2 + (kt >> 1));
                        else gate_load((pass - 2) * 2 + (kt >> 1));
                    }
                    if (!HELPER && pass == 2 && kt == 3) gate_load(4);
                    if (!HELPER && pass == 2 && kt == 4) gate_store(4);
                    const uint32_t rl_prev = rl;
                    rl = advance();
                    if (!passes) continue;
                    if (HELPER && kt != 2) {
                        wg_wait<1>();
                        if (job == 1) TR(120 + pass * 5 + kt - 1);
                        release_at<0>(rl_prev);
                        if (kt == 1 && pass == 3) release_at<24>(rel);
                    }
                    if (kt == 4 && !(HELPER && pass == 3)) mbar_wait(full + 8 * qs, qph);
                    wg_wait<0>();
                    if (!HELPER) TA(pass * 5 + kt);
                    if (HELPER && job == 1) TR(120 + pass * 5 + kt);
                    release_at<0>(rl);
                    if (!HELPER && kt < 3 && pass == 0) centre(kt + 1);
                }
                pin(acc);
                if (!HELPER && pass == 3) break;
                put(0);
                put(4);
                if (HELPER) TR(20 + job * 8 + 2 + pass);
                if (HELPER && pass == 3) {
                    __syncwarp();
                    if (lane == 0) mbar_arrive(qdone + 8 * job);
                    return;
                }
            }
            release_at<24>(rel);
            if (lane == 0) mbar_arrive(gated);
#pragma unroll
            for (int i = 0; i < 32; i++) {
                const float r = (i & 1) ? rd1 : rd0;
                q[i] = pack_bf16(acc[2 * i] * r, acc[2 * i + 1] * r);
            }
        };
        if (helper) {
            const uint32_t ep = sc->epoch[blockIdx.x] + 1;
            if (threadIdx.x < 160) {
                const uint32_t* w32 = (const uint32_t*)wr + (threadIdx.x >> 2) * 8 + (threadIdx.x & 3);
                asm volatile("st.shared.v2.u32 [%0], {%1, %2};" ::"r"(wperm + threadIdx.x * 8), "r"(__ldg(w32)), "r"(__ldg(w32 + 4)) : "memory");
            }
            asm volatile("bar.sync 3, 256;" ::: "memory");
            float ws[4] = {};
#pragma unroll 4
            for (int ks = 0; ks < 40; ks++) {
                uint32_t b0, b1;
                asm volatile("ld.shared.v2.u32 {%0, %1}, [%2];" : "=r"(b0), "=r"(b1) : "r"(wperm + (lane & 3) * 8 + ks * 32));
                hmma(ws, 0x3f803f80u, 0x3f803f80u, 0x3f803f80u, 0x3f803f80u, b0, b1);
            }
            wsum = ws[0];
            ep_tag = ep << 16;
            TR(0);
#pragma unroll 1
            for (int job = 0; job < 4; job++) {
                project(cint<1>(), job);
                TR(1 + job);
            }
            if (elect_one()) mbar_arrive(h1done);
            ffn_role(sc, ring, ffull, fempty, alldone, blockIdx.x - N_MAIN, ep, warp, x);
            return;
        }
        project(cint<0>(), 0);
        TR(2);
        TG(112);

        float o[64];
        uint32_t p[32];
        float l0, l1;
        constexpr float L_LO = 9.313225746154785e-10f, L_HI = 1.152921504606847e18f;
        float l_hi = L_HI;
        float (&s)[64] = acc;

        auto exp_range = [&](const float (&s)[64], int lo, int hi, float& u0, float& u1) {
            float w0 = 0.f, w1 = 0.f;
#pragma unroll
            for (int i = lo; i < hi; i += 4) {
                const float e0 = ex2(s[i]), e1 = ex2(s[i + 1]), e2 = ex2(s[i + 2]), e3 = ex2(s[i + 3]);
                u0 += e0; u1 += e2;
                if (i == lo) { w0 = e1; w1 = e3; } else { w0 += e1; w1 += e3; }
                p[i / 2] = pack_bf16(e0, e1); p[i / 2 + 1] = pack_bf16(e2, e3);
            }
            u0 += w0; u1 += w1;
        };
        auto unsafe = [&](bool first, float u0, float u1) {
            return (bool)__any_sync(0xffffffffu, !(u0 + u1 <= l_hi) || (first && !(fminf(u0, u1) >= L_LO)));
        };
        auto softmax_true_max = [&](const float (&s)[64], bool first, float b0, float b1, float& u0, float& u1) {
            uint32_t t;
            asm volatile("mov.u32 %0, %%tid.x;" : "=r"(t));
            uint4* const st = sc->rare + blockIdx.x * (17 * 256) + t;
            auto ld = [](const uint4* a) {
                uint4 v;
                asm volatile("ld.global.v4.u32 {%0, %1, %2, %3}, [%4];" : "=r"(v.x), "=r"(v.y), "=r"(v.z), "=r"(v.w) : "l"(a) : "memory");
                return v;
            };
#pragma unroll
            for (int i = 0; i < 16; i++)
                asm volatile("st.global.v4.f32 [%0], {%1, %2, %3, %4};" ::"l"(st + i * 256), "f"(s[4 * i]), "f"(s[4 * i + 1]), "f"(s[4 * i + 2]), "f"(s[4 * i + 3]) : "memory");
            float a0 = s[0], a1 = s[2];
#pragma unroll 1
            for (int i = 0; i < 16; i++) {
                const uint4 v = ld(st + i * 256);
                a0 = fmaxf(a0, fmaxf(__uint_as_float(v.x), __uint_as_float(v.y)));
                a1 = fmaxf(a1, fmaxf(__uint_as_float(v.z), __uint_as_float(v.w)));
            }
            float t0 = b0, t1 = b1, sg0 = 0.f, sg1 = 0.f;
            if (l_hi < 0.f) {
                const uint4 v = ld(st + 16 * 256);
                sg0 = __uint_as_float(v.x); sg1 = __uint_as_float(v.y);
            }
#pragma unroll
            for (int d = 1; d <= 2; d <<= 1) {
                a0 = fmaxf(a0, __shfl_xor_sync(0xffffffffu, a0, d)); a1 = fmaxf(a1, __shfl_xor_sync(0xffffffffu, a1, d));
                t0 += __shfl_xor_sync(0xffffffffu, t0, d); t1 += __shfl_xor_sync(0xffffffffu, t1, d);
            }
            if (!first) {
                a0 = fmaxf(a0, l_hi < 0.f ? sg0 : __log2f(t0)); a1 = fmaxf(a1, l_hi < 0.f ? sg1 : __log2f(t1));
            }
            const float al0 = first ? 1.f : ex2(sg0 - a0), al1 = first ? 1.f : ex2(sg1 - a1);
            asm volatile("st.global.v2.f32 [%0], {%1, %2};" ::"l"(st + 16 * 256), "f"(a0), "f"(a1) : "memory");
            l_hi = -1.f;
            u0 = b0 * al0; u1 = b1 * al1;
#pragma unroll 1
            for (int i = 0; i < 16; i++) {
                const uint4 v = ld(st + i * 256);
                const float e0 = ex2(__uint_as_float(v.x) - a0), e1 = ex2(__uint_as_float(v.y) - a0);
                const float e2 = ex2(__uint_as_float(v.z) - a1), e3 = ex2(__uint_as_float(v.w) - a1);
                u0 += e0 + e1; u1 += e2 + e3;
                asm volatile("st.global.v2.u32 [%0], {%1, %2};" ::"l"((uint2*)(st + (i >> 1) * 256) + (i & 1)), "r"(pack_bf16(e0, e1)), "r"(pack_bf16(e2, e3)) : "memory");
            }
#pragma unroll
            for (int i = 0; i < 8; i++) {
                const uint4 v = ld(st + i * 256);
                p[4 * i] = v.x; p[4 * i + 1] = v.y; p[4 * i + 2] = v.z; p[4 * i + 3] = v.w;
            }
            if (&s != &o) {
#pragma unroll
                for (int i = 0; i < 64; i++) o[i] *= (i & 2) ? al1 : al0;
            }
        };
        auto inv_sums = [&](float& i0, float& i1) {
            float a = l0, b = l1;
            a += __shfl_xor_sync(0xffffffffu, a, 1); b += __shfl_xor_sync(0xffffffffu, b, 1);
            a += __shfl_xor_sync(0xffffffffu, a, 2); b += __shfl_xor_sync(0xffffffffu, b, 2);
            i0 = rcp(a); i1 = rcp(b);
        };

        {
            bar_sync(my_bar);
            wg_fence();
            mma_tile<0>(o, q, ring16, 0);
            mbar_wait(full + 8, 0);
            wg_fence();
            mma_tile<0>(s, q, ring16 + T16, 0);
            bar_arrive(other_bar);
            wg_wait<1>();
            TA(20);
            release_at<0>(rel);
            pin(o);
            l0 = 0.f; l1 = 0.f;
            exp_range(o, 0, 64, l0, l1);
            mbar_wait(full + 16, 1);
            wg_wait<0>();
            if (RARE(unsafe(true, l0, l1))) softmax_true_max(o, true, 0.f, 0.f, l0, l1);
        }
        uint32_t qsrc = my_stash;
        float il0 = 0.f, il1 = 0.f;
        auto step = [&](auto odd_c, int m) {
            constexpr int ODD = decltype(odd_c)::value;
            constexpr int KS = ODD ? 3 : 1, VS = ODD ? 0 : 2;
            [[maybe_unused]] const int it = 2 * m + ODD;
            const uint32_t ph = m & 1;
            TC(0);
            bar_sync(my_bar);
            TC(1);
            if (ODD || m) {
                wg_fence();
                mma_tile<0>(s, q, ring16 + KS * T16, 0);
            }
            TC(2);
            if (!ODD) {
                if ((m & 7) == 0 && m) {
#pragma unroll
                    for (int i = FSPLIT; i < 8; i++)
                        sts128(qsrc + i * 512,
                               pack_bf16(o[8 * i] * il0, o[8 * i + 1] * il0), pack_bf16(o[8 * i + 2] * il1, o[8 * i + 3] * il1),
                               pack_bf16(o[8 * i + 4] * il0, o[8 * i + 5] * il0), pack_bf16(o[8 * i + 6] * il1, o[8 * i + 7] * il1));
                    qsrc += m == 24 ? -2 * TILE_BYTES : TILE_BYTES;
                }
                wg_fence();
            }
#pragma unroll
            for (int ks = 0; ks < 8; ks++) {
                wgmma_rs<1>(o, p[4 * ks], p[4 * ks + 1], p[4 * ks + 2], p[4 * ks + 3], desc_nmajor(ring16 + VS * T16, ks),
                            (ks == 0 && !ODD) ? ((m & 7) != 0) : 1);
                if (ks == SPLIT / 8 - 1 || ks == 7) wg_commit();
            }
            TC(3);
            bar_arrive(other_bar);
            const bool last = ODD && (m & 7) == 7;
            if (last) {
                inv_sums(il0, il1);
                l0 = 0.f; l1 = 0.f; l_hi = L_HI;
            }
            wg_wait<1>();
            TA(21 + it);
            TC(4);
            release_at<8 * KS>(rel);
            const bool newq = (m & 7) == 7;
            if (!ODD) {
                lds128_if<0>(newq, qsrc, q[0], q[1], q[2], q[3]);
                lds128_if<512>(newq, qsrc, q[4], q[5], q[6], q[7]);
                lds128_if<1024>(newq, qsrc, q[8], q[9], q[10], q[11]);
            }
            pin(s);
            float u0 = l0, u1 = l1;
            exp_range(s, 0, SPLIT, u0, u1);
            mbar_wait_hot(full + 8 * (KS ^ 2), ph ^ 1);
            if (!ODD) {
                lds128_if<1536>(newq, qsrc, q[12], q[13], q[14], q[15]);
                lds128_if<2048>(newq, qsrc, q[16], q[17], q[18], q[19]);
            }
            TC(5);
            wg_wait<0>();
            release_at<8 * VS>(rel);
            pin(o);
            exp_range(s, SPLIT, 64, u0, u1);
            TC(6);
            mbar_wait_hot(full + 8 * (VS ^ 2), ODD ? ph : ph ^ 1);
            if (!ODD) {
                lds128_if<2560>(newq, qsrc, q[20], q[21], q[22], q[23]);
                lds128_if<3072>(newq, qsrc, q[24], q[25], q[26], q[27]);
                lds128_if<3584>(newq, qsrc, q[28], q[29], q[30], q[31]);
            } else if (last) {
#pragma unroll
                for (int i = 0; i < FSPLIT; i++)
                    sts128(qsrc + i * 512,
                           pack_bf16(o[8 * i] * il0, o[8 * i + 1] * il0), pack_bf16(o[8 * i + 2] * il1, o[8 * i + 3] * il1),
                           pack_bf16(o[8 * i + 4] * il0, o[8 * i + 5] * il0), pack_bf16(o[8 * i + 6] * il1, o[8 * i + 7] * il1));
            }
            if (RARE(unsafe(last, u0, u1))) softmax_true_max(s, last, l0, l1, u0, u1);
            l0 = u0; l1 = u1;
            TC(7);
            TF(3 + it);
        };
#pragma unroll 1
        for (int m = 0;; m++) {
            step(cint<0>(), m);
            if (m == 31) break;
            step(cint<1>(), m);
        }
        uint32_t ob[64];
        const uint32_t t128 = threadIdx.x & 127;
        uint32_t ep, tag;
        const uint32_t half = 0x8000u;
        auto send = [&](uint4* dst, const float* a) {
            asm volatile("st.relaxed.gpu.global.v4.u32 [%0], {%1, %2, %3, %4};" ::"l"(dst), "r"(lop3<0xD8>(pack_bf16(a[0], a[1]), tag, 0x10000u)),
                         "r"(pack_bf16(a[2], a[3])), "r"(pack_bf16(a[4], a[5])), "r"(pack_bf16(a[6], a[7])) : "memory");
        };
        auto hint = [&](int dst, int job) {
            asm volatile("st.relaxed.gpu.global.u32 [%0], %1;" ::"l"((uint32_t*)(sc->flag + (qt * 8 + dst) * 32 + job) + (warp & 3)), "r"(ep) : "memory");
        };
        float a32[32], own[32];
        auto half_mma = [&](const uint32_t* a, const uint32_t* b, uint32_t t16, int accumulate) {
            wg_fence();
#pragma unroll
            for (int ks = 0; ks < 8; ks++) wgmma_rs64(a32, a[4 * ks], a[4 * ks + 1], a[4 * ks + 2], a[4 * ks + 3], desc_nmajor(t16, ks), ks ? 1 : accumulate);
#pragma unroll
            for (int ks = 0; ks < 8; ks++) wgmma_rs64(a32, b[4 * ks], b[4 * ks + 1], b[4 * ks + 2], b[4 * ks + 3], desc_nmajor(t16, 8 + ks), 1);
            wg_commit();
        };
        auto block_mma = [&](uint32_t sb, uint32_t ph, bool pass_turn) {
            mbar_wait(full + 8 * sb, ph);
            bar_sync(my_bar);
            half_mma(q, ob, ring16 + sb * T16, zero);
            mbar_wait(full + 8 * sb + 8, ph);
            half_mma(ob + 32, p, ring16 + (sb + 1) * T16, 1);
            if (pass_turn) bar_arrive(other_bar);
        };
        auto send_strips = [&](int u) {
            const uint32_t t = opaque(t128);
            const int d0 = (grp & 4) ^ (4 * u);
            uint4* dst = sc->part + (((qt * 8 + d0) * 9 + u) * 2 + wg) * 512 + (grp & 3) * 128 + t;
#pragma unroll
            for (int i = 0; i < 4; i++) send(dst + i * 9 * 1024, a32 + 8 * i);
            if ((t & 31) < 4) hint(d0 + (t & 31), u * 8 + (grp & 3) * 2 + wg);
        };
        uint32_t xs[4], gs[4];
        {
            [[maybe_unused]] const int c = 9;
            TS(0);
            auto fetch_o = [&](int lo, int hi) {
#pragma unroll
                for (int i = lo; i < hi; i++)
                    lds128(qsrc + (1 + (i >> 3)) * TILE_BYTES + (i & 7) * 512, ob[4 * i], ob[4 * i + 1], ob[4 * i + 2], ob[4 * i + 3]);
            };
            fetch_o(0, 3);
            bar_sync(my_bar);
            wg_fence();
            mma_tile<1>(o, p, ring16 + 3 * T16, 1);
            sched_fence(zero);
            inv_sums(il0, il1);
            asm volatile("" : "+f"(il0), "+f"(il1));
            sched_fence(zero);
            fetch_o(3, 6);
            wg_fence();
#pragma unroll
            for (int ks = 0; ks < 8; ks++) {
                wgmma_rs64(a32, q[4 * ks], q[4 * ks + 1], q[4 * ks + 2], q[4 * ks + 3], desc_nmajor(ring16, ks), ks);
                if (ks == 3) { wg_commit(); sched_fence(zero); fetch_o(6, 8); wg_fence(); }
            }
            TS(1);
#pragma unroll
            for (int ks = 0; ks < 8; ks++) wgmma_rs64(a32, ob[4 * ks], ob[4 * ks + 1], ob[4 * ks + 2], ob[4 * ks + 3], desc_nmajor(ring16, 8 + ks), 1);
            wg_commit();
            TS(2);
            bar_arrive(other_bar);
            wg_wait<1>();
            release_at<24>(rel);
            pin(o);
#pragma unroll
            for (int i = 0; i < 32; i++) {
                const float r = (i & 1) ? il1 : il0;
                asm volatile("cvt.rn.bf16x2.f32 %0, %1, %2;" : "=r"(p[i]) : "f"(o[2 * i + 1] * r), "f"(o[2 * i] * r));
                if ((i & 7) == 7) fetch_o(8 + (i >> 3) * 2, 10 + (i >> 3) * 2);
            }
            TS(3);
            mbar_wait(full + 8, 0);
            wg_wait<0>();
            release_at<0>(rel);
            __syncwarp();
            if (lane == 0) mbar_arrive(vacant);
            TS(4);
            bar_sync(my_bar);
            half_mma(ob + 32, p, ring16 + T16, 1);
            TS(5);
            bar_arrive(other_bar);
            TR(66);
            TG(113);
            mbar_wait(routed, 0);
            asm volatile("ld.shared.u32 %0, [%1];" : "=r"(ep) : "r"(epoch));
            tag = ep << 16;
            const uint4* src = sc->gate + (blockIdx.x * 5 + 4) * 512 + threadIdx.x;
            asm volatile("ld.global.cg.v4.u32 {%0, %1, %2, %3}, [%4];" : "=r"(xs[0]), "=r"(xs[1]), "=r"(xs[2]), "=r"(xs[3]) : "l"(src));
            asm volatile("ld.global.cg.v4.u32 {%0, %1, %2, %3}, [%4];" : "=r"(gs[0]), "=r"(gs[1]), "=r"(gs[2]), "=r"(gs[3]) : "l"(src + 256));
            sched_fence(zero);
            wg_wait<0>();
            TS(6);
            release_at<8>(rel);
            pin(a32);
            send_strips(0);
            TS(7);
        }
        uint32_t v[4][4];
        auto stale = [&]() {
            return __any_sync(0xffffffffu, lop3<0xA8>(lop3<0x7E>(v[0][0], v[1][0], tag), lop3<0x7E>(v[2][0], v[3][0], tag), 0x10000u));
        };
        auto recv = [&](int u) {
            mbar_wait(rfull + 16 * u + 8 * wg, 0);
#pragma unroll
            for (int i = 0; i < 4; i++)
                lds128(stash + (u >= 6 ? u - 6 : u) * 16384 + wg * 8192 + i * 2048 + t128 * 16, v[i][0], v[i][1], v[i][2], v[i][3]);
            if (stale()) {
                const uint4* src = sc->part + (((qt * 8 + grp) * 9 + u) * 2 + wg) * 512 + opaque(t128);
                do {
#pragma unroll
                    for (int i = 0; i < 4; i++)
                        asm volatile("ld.relaxed.gpu.global.v4.u32 {%0, %1, %2, %3}, [%4];" : "=r"(v[i][0]), "=r"(v[i][1]), "=r"(v[i][2]), "=r"(v[i][3])
                                     : "l"(src + i * 128) : "memory");
                } while (stale());
            }
            if (u < 3 && lane == 0) mbar_arrive(rdone + (u * 2 + wg) * 8);
        };
        auto accumulate = [&](float* dst, int stride) {
#pragma unroll
            for (int i = 0; i < 4; i++) {
                float* a = dst + stride * i;
                a[0] += bf_lo(v[i][0]);
                a[1] += __uint_as_float(lop3<0xEC>(v[i][0], half, 0xfffe0000u));
#pragma unroll
                for (int k = 1; k < 4; k++) { a[2 * k] += bf_lo(v[i][k]); a[2 * k + 1] += bf_hi(v[i][k]); }
            }
        };
        auto gate = [](uint32_t x2, uint32_t g2, float lo, float hi) {
            uint32_t sv = pack_bf16(lo, hi);
            asm("mul.rn.bf16x2 %0, %0, %1;" : "+r"(sv) : "r"(g2));
            asm("add.rn.bf16x2 %0, %0, %1;" : "+r"(sv) : "r"(x2));
            return sv;
        };
        uint4* const outbox = sc->part + qt * (8 * 9 * 1024) + wg * 512 + t128;
        auto step_o = [&](int f) {
            [[maybe_unused]] const int c = f;
            const uint32_t sb = (f & 1) ? 0 : 2;
            block_mma(sb, (((f + 3) >> 1) ^ f) & 1, true);
            wg_wait<1>();
            const uint32_t rl = rel && f < 7 ? rel + 8 * sb : 0;
            release_at<0>(rl);
            if (f >= 1) recv(f - 1);
            wg_wait<0>();
            TS(0);
            release_at<8>(rl);
            pin(a32);
            if (f == 0) {
                send_strips(1);
            } else {
                const int d = (grp + f) & 7;
#pragma unroll
                for (int i = 0; i < 4; i++) send(outbox + (d * 9 + f + 1) * 1024 + i * 128, a32 + 8 * i);
                if (lane == 0) hint(d, 14 + 2 * f + wg);
            }
            TS(1);
        };
        {
            float st[8] = {};
#pragma unroll 1
            for (int f = 0; f < 3; f++) {
                [[maybe_unused]] const int c = f;
                step_o(f);
                if (f >= 1) accumulate(st, 0);
                TS(2);
            }
            uint32_t w[4];
#pragma unroll
            for (int i = 0; i < 4; i++) w[i] = gate(xs[i], gs[i], st[2 * i], st[2 * i + 1]);
            const bool odd = lane & 1;
            const uint32_t r0 = __shfl_xor_sync(0xffffffffu, odd ? w[0] : w[2], 1), r1 = __shfl_xor_sync(0xffffffffu, odd ? w[1] : w[3], 1);
            uint2* dst = (uint2*)out + (qt * 128 + warp * 16 + (lane >> 2)) * (DM / 4) + 128 + grp * 4 + (lane & 1) * 2 + ((lane >> 1) & 1);
            dst[0] = odd ? make_uint2(r0, w[2]) : make_uint2(w[0], r0);
            dst[2 * DM] = odd ? make_uint2(r1, w[3]) : make_uint2(w[1], r1);
        }
#pragma unroll
        for (int i = 0; i < 32; i++) own[i] = 0.f;
#pragma unroll 1
        for (int f = 3; f < 8; f++) {
            [[maybe_unused]] const int c = f;
            step_o(f);
            accumulate(own, 8);
            TS(2);
        }
        {
            [[maybe_unused]] const int c = 8;
            recv(7);
            accumulate(own, 8);
            TS(7);
            block_mma(2, 1, wg == 0);
            TR(71);
            TS(0);
            recv(8);
            accumulate(own, 8);
            TS(1);
            wg_wait<1>();
            uint32_t xv[16], gv[16];
            mbar_wait(xgfull, 0);
            if (lane == 0) mbar_arrive(alldone);
#pragma unroll
            for (int j = 0; j < 4; j++) {
                lds128(stash + 3 * 16384 + j * 8192 + threadIdx.x * 16, xv[4 * j], xv[4 * j + 1], xv[4 * j + 2], xv[4 * j + 3]);
                lds128(stash + 3 * 16384 + j * 8192 + 4096 + threadIdx.x * 16, gv[4 * j], gv[4 * j + 1], gv[4 * j + 2], gv[4 * j + 3]);
            }
            TS(2);
            wg_wait<0>();
            pin(a32);
#pragma unroll
            for (int i = 0; i < 32; i++) own[i] += a32[i];
            TS(3);
            const uint32_t tb = ring + warp * 2048;
#pragma unroll
            for (int j = 0; j < 4; j++)
                stsm4(tb + (lane & 15) * 128 + (((2 * j + (lane >> 4)) ^ (lane & 7)) << 4),
                      gate(xv[4 * j], gv[4 * j], own[8 * j], own[8 * j + 1]), gate(xv[4 * j + 1], gv[4 * j + 1], own[8 * j + 2], own[8 * j + 3]),
                      gate(xv[4 * j + 2], gv[4 * j + 2], own[8 * j + 4], own[8 * j + 5]), gate(xv[4 * j + 3], gv[4 * j + 3], own[8 * j + 6], own[8 * j + 7]));
            __syncwarp();
#pragma unroll
            for (int j = 0; j < 4; j++) {
                const uint32_t row = j * 4 + (lane >> 3);
                uint4 v;
                lds128(tb + row * 128 + (((lane & 7) ^ (row & 7)) << 4), v.x, v.y, v.z, v.w);
                ((uint4*)out)[(qt * 128 + warp * 16 + row) * (DM / 8) + grp * 8 + (lane & 7)] = v;
            }
        }
        TR(73);
        TG(111);
    }
}

typedef CUresult (*EncodeFn)(CUtensorMap*, CUtensorMapDataType, cuuint32_t, void*, const cuuint64_t*, const cuuint64_t*,
                             const cuuint32_t*, const cuuint32_t*, CUtensorMapInterleave, CUtensorMapSwizzle,
                             CUtensorMapL2promotion, CUtensorMapFloatOOBfill);

void make_map(EncodeFn enc, CUtensorMap* tm, const void* ptr, uint64_t cols, uint64_t rows) {
    cuuint64_t gd[2] = {cols, rows};
    cuuint64_t gs[1] = {cols * 2};
    cuuint32_t bd[2] = {64, 128};
    cuuint32_t es[2] = {1, 1};
    enc(tm, CU_TENSOR_MAP_DATA_TYPE_BFLOAT16, 2, const_cast<void*>(ptr), gd, gs, bd, es, CU_TENSOR_MAP_INTERLEAVE_NONE,
        CU_TENSOR_MAP_SWIZZLE_128B, CU_TENSOR_MAP_L2_PROMOTION_L2_256B, CU_TENSOR_MAP_FLOAT_OOB_FILL_NONE);
}

}

extern "C" void kernel_launch(void* const* d_in, const int* in_sizes, int n_in, void* d_out, int out_size) {
    const __nv_bfloat16* x = (const __nv_bfloat16*)d_in[0];
    const __nv_bfloat16* wr = (const __nv_bfloat16*)d_in[6];
    __nv_bfloat16* out = (__nv_bfloat16*)d_out;

    EncodeFn enc = nullptr;
    cudaDriverEntryPointQueryResult qr;
    cudaGetDriverEntryPoint("cuTensorMapEncodeTiled", (void**)&enc, cudaEnableDefault, &qr);
    CUtensorMap tm_x, tm_wq, tm_k, tm_v, tm_wo, tm_g, tm_u, tm_d;
    {
        cuuint64_t gd[3] = {64, SEQ, DM / 64};
        cuuint64_t gs[2] = {DM * 2, 128};
        cuuint32_t bd[3] = {64, 64, 2};
        cuuint32_t es[3] = {1, 1, 1};
        enc(&tm_x, CU_TENSOR_MAP_DATA_TYPE_BFLOAT16, 3, d_in[0], gd, gs, bd, es, CU_TENSOR_MAP_INTERLEAVE_NONE,
            CU_TENSOR_MAP_SWIZZLE_128B, CU_TENSOR_MAP_L2_PROMOTION_L2_256B, CU_TENSOR_MAP_FLOAT_OOB_FILL_NONE);
    }
    make_map(enc, &tm_k, d_in[1], DH, (uint64_t)NH * SEQ);
    make_map(enc, &tm_v, d_in[2], DH, (uint64_t)NH * SEQ);
    make_map(enc, &tm_wq, d_in[3], NH * DH, DM);
    make_map(enc, &tm_wo, d_in[4], DM, NH * DH);
    make_map(enc, &tm_g, d_in[7], FF, DM);
    make_map(enc, &tm_u, d_in[8], FF, DM);
    make_map(enc, &tm_d, d_in[9], DM, FF);
    cudaFuncSetAttribute(fused_attn_kernel, cudaFuncAttributeMaxDynamicSharedMemorySize, SMEM_BYTES);

    Scratch* sc = nullptr;
    cudaGetSymbolAddress((void**)&sc, g_scratch);

    cudaLaunchConfig_t cfg = {};
    cfg.gridDim = dim3(N_MAIN + N_MOE);
    cfg.blockDim = dim3(384);
    cfg.dynamicSmemBytes = SMEM_BYTES;
    cfg.stream = cudaStreamPerThread;
    cudaLaunchAttribute at[1];
    at[0].id = cudaLaunchAttributeClusterDimension;
    at[0].val.clusterDim.x = 2; at[0].val.clusterDim.y = 1; at[0].val.clusterDim.z = 1;
    cfg.attrs = at; cfg.numAttrs = 1;
    cudaLaunchKernelEx(&cfg, fused_attn_kernel, x, wr, out, sc, tm_x, tm_wq, tm_k, tm_v, tm_wo, tm_g, tm_u, tm_d);
}
```

```cpp
#include <cuda_runtime.h>
#include <cuda.h>
#include <cuda_bf16.h>
#include <stdint.h>

namespace {

constexpr int SEQ = 2048, DM = 640, NH = 32, DH = 128, FF = 1728, CAP = 8;
constexpr int NSLOT = 4;
constexpr int TILE_BYTES = 32768;
constexpr uint32_t RING_OFFSET = 1024;
constexpr int SMEM_BYTES = (NSLOT + 3) * TILE_BYTES + 416 + 1408 + 96;
constexpr int N_MAIN = 128, N_MOE = 4;

struct Scratch {
    uint4 part[16 * 8 * 9 * 2 * 4 * 128];
    uint4 gate[N_MAIN * 5 * 2 * 256];
    uint4 flag[16 * 8 * 32];
    uint4 qoff[16 * 4 * 2048];
    uint32_t flag_q[16];
    uint4 rare[N_MAIN * 17 * 256];
    float y[N_MOE * CAP * DM];
    uint2 routed[CAP * DM / 4];
    uint2 stat[SEQ];
    float r[SEQ];
    int idx[CAP];
    uint32_t flag_r[N_MOE], flag_y[N_MOE], flag_u[N_MOE];
    uint32_t epoch[N_MAIN + N_MOE];
};
__device__ Scratch g_scratch;

__device__ __forceinline__ uint32_t smem_u32(const void* p) { return (uint32_t)__cvta_generic_to_shared(p); }
__device__ __forceinline__ void mbar_init(uint32_t bar, uint32_t cnt) {
    asm volatile("mbarrier.init.shared::cta.b64 [%0], %1;" ::"r"(bar), "r"(cnt) : "memory");
}
#define HOTW 2
__device__ __forceinline__ void mbar_wait(uint32_t bar, uint32_t parity) {
    asm volatile(
        "{\n.reg .pred p;\n"
        "LOOP:\n"
        "mbarrier.try_wait.parity.shared::cta.b64 p, [%0], %1;\n"
        "@!p bra.uni LOOP;\n"
        "DONE:\n}\n" ::"r"(bar), "r"(parity) : "memory");
}
__device__ __forceinline__ void mbar_wait_hot(uint32_t bar, uint32_t parity) {
    asm volatile(
        "{\n.reg .pred p;\n.reg .u32 c;\n"
        "mbarrier.test_wait.parity.shared::cta.b64 p, [%0], %1;\n"
        "@p bra.uni DONE;\n"
        "mov.u32 c, 0;\n"
        "LOOP:\n"
        "mbarrier.try_wait.parity.shared::cta.b64 p, [%0], %1;\n"
        "@p bra.uni DONE;\n"
        "add.u32 c, c, 1;\n"
        "setp.lt.u32 p, c, 2000000;\n"
        "@p bra.uni LOOP;\n"
        "trap;\n"
        "DONE:\n}\n" ::"r"(bar), "r"(parity) : "memory");
}
__device__ __forceinline__ void mbar_wait_bounded(uint32_t bar, uint32_t parity) {
    asm volatile(
        "{\n.reg .pred p;\n.reg .u32 c;\n"
        "mov.u32 c, 0;\n"
        "LOOP:\n"
        "mbarrier.try_wait.parity.shared::cta.b64 p, [%0], %1;\n"
        "@p bra.uni DONE;\n"
        "add.u32 c, c, 1;\n"
        "setp.lt.u32 p, c, 2000000;\n"
        "@p bra.uni LOOP;\n"
        "trap;\n"
        "DONE:\n}\n" ::"r"(bar), "r"(parity) : "memory");
}
__device__ __forceinline__ void mbar_wait_sleep(uint32_t bar, uint32_t parity) {
    asm volatile(
        "{\n.reg .pred p;\n.reg .u32 c;\n"
        "mov.u32 c, 0;\n"
        "LOOP:\n"
        "mbarrier.test_wait.parity.shared::cta.b64 p, [%0], %1;\n"
        "@p bra.uni DONE;\n"
        "nanosleep.u32 500;\n"
        "add.u32 c, c, 1;\n"
        "setp.lt.u32 p, c, 1000000;\n"
        "@p bra.uni LOOP;\n"
        "trap;\n"
        "DONE:\n}\n" ::"r"(bar), "r"(parity) : "memory");
}
__device__ __forceinline__ void mbar_expect_tx(uint32_t bar, uint32_t bytes) {
    asm volatile("mbarrier.arrive.expect_tx.shared::cta.b64 _, [%0], %1;" ::"r"(bar), "r"(bytes) : "memory");
}
template <int OFF>
__device__ __forceinline__ void release_at(uint32_t bar) {
    asm volatile(
        "{\n.reg .pred p;\n"
        "setp.ne.u32 p, %0, 0;\n"
        "@p mbarrier.arrive.shared::cluster.b64 _, [%0 + %1];\n}\n" ::"r"(bar), "n"(OFF) : "memory");
}
__device__ __forceinline__ void sched_fence(int zero) {
    asm volatile("{\n.reg .pred p;\n.reg .u32 c;\nsetp.ne.s32 p, %0, 0;\n@p mov.u32 c, %%clock;\n@p st.shared.u32 [%0], c;\n}\n" ::"r"(zero) : "memory");
}
__device__ __forceinline__ bool elect_one() {
    uint32_t r;
    asm volatile("{\n.reg .pred p;\nelect.sync _|p, 0xffffffff;\nselp.u32 %0, 1, 0, p;\n}\n" : "=r"(r));
    return r;
}
__device__ __forceinline__ uint32_t opaque(uint32_t v) {
    uint32_t r;
    asm volatile("mov.u32 %0, %1;" : "=r"(r) : "r"(v));
    return r;
}
__device__ __forceinline__ void tma_2d(uint32_t dst, const CUtensorMap* tm, uint32_t bar, int c0, int c1) {
    asm volatile(
        "cp.async.bulk.tensor.2d.shared::cluster.global.mbarrier::complete_tx::bytes [%0], [%1, {%3, %4}], [%2];"
        ::"r"(dst), "l"(tm), "r"(bar), "r"(c0), "r"(c1) : "memory");
}
__device__ __forceinline__ void tma_3d(uint32_t dst, const CUtensorMap* tm, uint32_t bar, int c0, int c1, int c2) {
    asm volatile(
        "cp.async.bulk.tensor.3d.shared::cluster.global.mbarrier::complete_tx::bytes [%0], [%1, {%3, %4, %5}], [%2];"
        ::"r"(dst), "l"(tm), "r"(bar), "r"(c0), "r"(c1), "r"(c2) : "memory");
}
__device__ __forceinline__ void tma_2d_mc(uint32_t dst, const CUtensorMap* tm, uint32_t bar, int c0, int c1) {
    asm volatile(
        "cp.async.bulk.tensor.2d.shared::cluster.global.mbarrier::complete_tx::bytes.multicast::cluster "
        "[%0], [%1, {%3, %4}], [%2], %5;"
        ::"r"(dst), "l"(tm), "r"(bar), "r"(c0), "r"(c1), "h"((uint16_t)3) : "memory");
}
__device__ __forceinline__ void tma_prefetch(const CUtensorMap* tm, int c0, int c1) {
    asm volatile("cp.async.bulk.prefetch.tensor.2d.L2.global [%0, {%1, %2}];" ::"l"(tm), "r"(c0), "r"(c1) : "memory");
}
__device__ __forceinline__ void mbar_arrive(uint32_t bar) {
    asm volatile("mbarrier.arrive.shared::cta.b64 _, [%0];" ::"r"(bar) : "memory");
}
__device__ __forceinline__ void flag_set(uint32_t* f, uint32_t v) {
    asm volatile("st.release.gpu.global.u32 [%0], %1;" ::"l"(f), "r"(v) : "memory");
}
template <int SLEEP_NS = 0>
__device__ __forceinline__ void flag_wait(const uint32_t* f, uint32_t v) {
    asm volatile(
        "{\n.reg .pred p;\n.reg .u32 c;\n"
        "LOOP:\n"
        "setp.ne.u32 p, %2, 0;\n"
        "@p nanosleep.u32 %2;\n"
        "ld.acquire.gpu.global.u32 c, [%0];\n"
        "setp.ne.u32 p, c, %1;\n"
        "@p bra LOOP;\n}\n" ::"l"(f), "r"(v), "n"(SLEEP_NS) : "memory");
}
template <int SLEEP_NS>
__device__ __forceinline__ void flag_wait_bounded(const uint32_t* f, uint32_t v) {
    asm volatile(
        "{\n.reg .pred p;\n.reg .u32 c, n;\n"
        "mov.u32 n, 0;\n"
        "LOOP:\n"
        "setp.ne.u32 p, %2, 0;\n"
        "@p nanosleep.u32 %2;\n"
        "ld.acquire.gpu.global.u32 c, [%0];\n"
        "setp.eq.u32 p, c, %1;\n"
        "@p bra DONE;\n"
        "add.u32 n, n, 1;\n"
        "setp.lt.u32 p, n, %3;\n"
        "@p bra LOOP;\n"
        "trap;\n"
        "DONE:\n}\n" ::"l"(f), "r"(v), "n"(SLEEP_NS), "n"(2000000) : "memory");
}
__device__ __forceinline__ void hmma(float (&d)[4], uint32_t a0, uint32_t a1, uint32_t a2, uint32_t a3, uint32_t b0, uint32_t b1) {
    asm volatile("mma.sync.aligned.m16n8k16.row.col.f32.bf16.bf16.f32 {%0,%1,%2,%3}, {%4,%5,%6,%7}, {%8,%9}, {%0,%1,%2,%3};"
                 : "+f"(d[0]), "+f"(d[1]), "+f"(d[2]), "+f"(d[3]) : "r"(a0), "r"(a1), "r"(a2), "r"(a3), "r"(b0), "r"(b1));
}
__device__ __forceinline__ void hmma8(float (&d)[4], uint32_t a0, uint32_t a1, uint32_t b0) {
    asm volatile("mma.sync.aligned.m16n8k8.row.col.f32.bf16.bf16.f32 {%0,%1,%2,%3}, {%4,%5}, {%6}, {%0,%1,%2,%3};"
                 : "+f"(d[0]), "+f"(d[1]), "+f"(d[2]), "+f"(d[3]) : "r"(a0), "r"(a1), "r"(b0));
}
__device__ __forceinline__ void ldsm4(uint32_t addr, uint32_t& a, uint32_t& b, uint32_t& c, uint32_t& d) {
    asm volatile("ldmatrix.sync.aligned.m8n8.x4.shared.b16 {%0, %1, %2, %3}, [%4];"
                 : "=r"(a), "=r"(b), "=r"(c), "=r"(d) : "r"(addr) : "memory");
}
__device__ __forceinline__ void stsm4(uint32_t addr, uint32_t a, uint32_t b, uint32_t c, uint32_t d) {
    asm volatile("stmatrix.sync.aligned.m8n8.x4.shared.b16 [%4], {%0, %1, %2, %3};"
                 ::"r"(a), "r"(b), "r"(c), "r"(d), "r"(addr) : "memory");
}
__device__ __forceinline__ uint32_t bf2_sub(uint32_t a, uint32_t b) {
    uint32_t d;
    asm("sub.rn.bf16x2 %0, %1, %2;" : "=r"(d) : "r"(a), "r"(b));
    return d;
}
template <int LUT>
__device__ __forceinline__ uint32_t lop3(uint32_t a, uint32_t b, uint32_t c) {
    uint32_t d;
    asm("lop3.b32 %0, %1, %2, %3, %4;" : "=r"(d) : "r"(a), "r"(b), "r"(c), "n"(LUT));
    return d;
}
__device__ __forceinline__ float rcp(float x) {
    float y;
    asm("rcp.approx.ftz.f32 %0, %1;" : "=f"(y) : "f"(x));
    return y;
}
__device__ __forceinline__ void bar_sync(int id) { asm volatile("bar.sync %0, 256;" ::"r"(id) : "memory"); }
__device__ __forceinline__ void bar_arrive(int id) { asm volatile("bar.arrive %0, 256;" ::"r"(id) : "memory"); }
__device__ __forceinline__ void wg_fence() { asm volatile("wgmma.fence.sync.aligned;" ::: "memory"); }
__device__ __forceinline__ void wg_commit() { asm volatile("wgmma.commit_group.sync.aligned;" ::: "memory"); }
template <int N> __device__ __forceinline__ void wg_wait() { asm volatile("wgmma.wait_group.sync.aligned %0;" ::"n"(N) : "memory"); }
template <int N>
__device__ __forceinline__ void pin(float (&d)[N]) {
#pragma unroll
    for (int i = 0; i < N; i++) asm volatile("" : "+f"(d[i])::"memory");
}
__device__ __forceinline__ uint32_t pack_bf16(float lo, float hi) {
    uint32_t r;
    asm("cvt.rn.bf16x2.f32 %0, %1, %2;" : "=r"(r) : "f"(hi), "f"(lo));
    return r;
}
__device__ __forceinline__ float bf_lo(uint32_t v) { return __uint_as_float(v << 16); }
__device__ __forceinline__ float bf_hi(uint32_t v) { return __uint_as_float(v & 0xffff0000u); }
__device__ __forceinline__ float bf_round(float v) { return __bfloat162float(__float2bfloat16_rn(v)); }
__device__ __forceinline__ float ex2(float x) {
    float y;
    asm("ex2.approx.ftz.f32 %0, %1;" : "=f"(y) : "f"(x));
    return y;
}
__device__ __forceinline__ void sts128(uint32_t addr, uint32_t a, uint32_t b, uint32_t c, uint32_t d) {
    asm volatile("st.shared.v4.b32 [%0], {%1, %2, %3, %4};" ::"r"(addr), "r"(a), "r"(b), "r"(c), "r"(d) : "memory");
}
__device__ __forceinline__ void lds128(uint32_t addr, uint32_t& a, uint32_t& b, uint32_t& c, uint32_t& d) {
    asm volatile("ld.shared.v4.b32 {%0, %1, %2, %3}, [%4];" : "=r"(a), "=r"(b), "=r"(c), "=r"(d) : "r"(addr) : "memory");
}

template <int OFF>
__device__ __forceinline__ void lds128_if(bool on, uint32_t addr, uint32_t& a, uint32_t& b, uint32_t& c, uint32_t& d) {
    asm volatile("{\n.reg .pred p;\nsetp.ne.u32 p, %5, 0;\n@p ld.shared.v4.b32 {%0, %1, %2, %3}, [%4 + %6];\n}\n"
                 : "+r"(a), "+r"(b), "+r"(c), "+r"(d) : "r"(addr), "r"((uint32_t)on), "n"(OFF) : "memory");
}

template <int TB>
__device__ __forceinline__ void wgmma_rs(float (&d)[64], uint32_t a0, uint32_t a1, uint32_t a2, uint32_t a3,
                                         uint64_t desc, int scale_d) {
    asm volatile(
        "{\n.reg .pred p;\nsetp.ne.b32 p, %69, 0;\n"
        "wgmma.mma_async.sync.aligned.m64n128k16.f32.bf16.bf16 "
        "{%0,%1,%2,%3,%4,%5,%6,%7,%8,%9,%10,%11,%12,%13,%14,%15,%16,%17,%18,%19,%20,%21,%22,%23,%24,%25,%26,%27,%28,%29,%30,%31,"
        "%32,%33,%34,%35,%36,%37,%38,%39,%40,%41,%42,%43,%44,%45,%46,%47,%48,%49,%50,%51,%52,%53,%54,%55,%56,%57,%58,%59,%60,%61,%62,%63},"
        "{%64,%65,%66,%67}, %68, p, 1, 1, %70;\n}\n"
        : "+f"(d[0]), "+f"(d[1]), "+f"(d[2]), "+f"(d[3]), "+f"(d[4]), "+f"(d[5]), "+f"(d[6]), "+f"(d[7]),
          "+f"(d[8]), "+f"(d[9]), "+f"(d[10]), "+f"(d[11]), "+f"(d[12]), "+f"(d[13]), "+f"(d[14]), "+f"(d[15]),
          "+f"(d[16]), "+f"(d[17]), "+f"(d[18]), "+f"(d[19]), "+f"(d[20]), "+f"(d[21]), "+f"(d[22]), "+f"(d[23]),
          "+f"(d[24]), "+f"(d[25]), "+f"(d[26]), "+f"(d[27]), "+f"(d[28]), "+f"(d[29]), "+f"(d[30]), "+f"(d[31]),
          "+f"(d[32]), "+f"(d[33]), "+f"(d[34]), "+f"(d[35]), "+f"(d[36]), "+f"(d[37]), "+f"(d[38]), "+f"(d[39]),
          "+f"(d[40]), "+f"(d[41]), "+f"(d[42]), "+f"(d[43]), "+f"(d[44]), "+f"(d[45]), "+f"(d[46]), "+f"(d[47]),
          "+f"(d[48]), "+f"(d[49]), "+f"(d[50]), "+f"(d[51]), "+f"(d[52]), "+f"(d[53]), "+f"(d[54]), "+f"(d[55]),
          "+f"(d[56]), "+f"(d[57]), "+f"(d[58]), "+f"(d[59]), "+f"(d[60]), "+f"(d[61]), "+f"(d[62]), "+f"(d[63])
        : "r"(a0), "r"(a1), "r"(a2), "r"(a3), "l"(desc), "r"(scale_d), "n"(TB));
}
__device__ __forceinline__ void wgmma_ss(float (&d)[64], uint64_t desc_a, uint64_t desc_b, int scale_d) {
    asm volatile(
        "{\n.reg .pred p;\nsetp.ne.b32 p, %66, 0;\n"
        "wgmma.mma_async.sync.aligned.m64n128k16.f32.bf16.bf16 "
        "{%0,%1,%2,%3,%4,%5,%6,%7,%8,%9,%10,%11,%12,%13,%14,%15,%16,%17,%18,%19,%20,%21,%22,%23,%24,%25,%26,%27,%28,%29,%30,%31,"
        "%32,%33,%34,%35,%36,%37,%38,%39,%40,%41,%42,%43,%44,%45,%46,%47,%48,%49,%50,%51,%52,%53,%54,%55,%56,%57,%58,%59,%60,%61,%62,%63},"
        "%64, %65, p, 1, 1, 0, 1;\n}\n"
        : "+f"(d[0]), "+f"(d[1]), "+f"(d[2]), "+f"(d[3]), "+f"(d[4]), "+f"(d[5]), "+f"(d[6]), "+f"(d[7]),
          "+f"(d[8]), "+f"(d[9]), "+f"(d[10]), "+f"(d[11]), "+f"(d[12]), "+f"(d[13]), "+f"(d[14]), "+f"(d[15]),
          "+f"(d[16]), "+f"(d[17]), "+f"(d[18]), "+f"(d[19]), "+f"(d[20]), "+f"(d[21]), "+f"(d[22]), "+f"(d[23]),
          "+f"(d[24]), "+f"(d[25]), "+f"(d[26]), "+f"(d[27]), "+f"(d[28]), "+f"(d[29]), "+f"(d[30]), "+f"(d[31]),
          "+f"(d[32]), "+f"(d[33]), "+f"(d[34]), "+f"(d[35]), "+f"(d[36]), "+f"(d[37]), "+f"(d[38]), "+f"(d[39]),
          "+f"(d[40]), "+f"(d[41]), "+f"(d[42]), "+f"(d[43]), "+f"(d[44]), "+f"(d[45]), "+f"(d[46]), "+f"(d[47]),
          "+f"(d[48]), "+f"(d[49]), "+f"(d[50]), "+f"(d[51]), "+f"(d[52]), "+f"(d[53]), "+f"(d[54]), "+f"(d[55]),
          "+f"(d[56]), "+f"(d[57]), "+f"(d[58]), "+f"(d[59]), "+f"(d[60]), "+f"(d[61]), "+f"(d[62]), "+f"(d[63])
        : "l"(desc_a), "l"(desc_b), "r"(scale_d));
}
__device__ __forceinline__ void wgmma_rs64(float (&d)[32], uint32_t a0, uint32_t a1, uint32_t a2, uint32_t a3,
                                           uint64_t desc, int scale_d) {
    asm volatile(
        "{\n.reg .pred p;\nsetp.ne.b32 p, %37, 0;\n"
        "wgmma.mma_async.sync.aligned.m64n64k16.f32.bf16.bf16 "
        "{%0,%1,%2,%3,%4,%5,%6,%7,%8,%9,%10,%11,%12,%13,%14,%15,%16,%17,%18,%19,%20,%21,%22,%23,%24,%25,%26,%27,%28,%29,%30,%31},"
        "{%32,%33,%34,%35}, %36, p, 1, 1, 1;\n}\n"
        : "+f"(d[0]), "+f"(d[1]), "+f"(d[2]), "+f"(d[3]), "+f"(d[4]), "+f"(d[5]), "+f"(d[6]), "+f"(d[7]),
          "+f"(d[8]), "+f"(d[9]), "+f"(d[10]), "+f"(d[11]), "+f"(d[12]), "+f"(d[13]), "+f"(d[14]), "+f"(d[15]),
          "+f"(d[16]), "+f"(d[17]), "+f"(d[18]), "+f"(d[19]), "+f"(d[20]), "+f"(d[21]), "+f"(d[22]), "+f"(d[23]),
          "+f"(d[24]), "+f"(d[25]), "+f"(d[26]), "+f"(d[27]), "+f"(d[28]), "+f"(d[29]), "+f"(d[30]), "+f"(d[31])
        : "r"(a0), "r"(a1), "r"(a2), "r"(a3), "l"(desc), "r"(scale_d));
}
__device__ __forceinline__ void wgmma_ss64(float (&d)[32], uint64_t desc_a, uint64_t desc_b, int scale_d) {
    asm volatile(
        "{\n.reg .pred p;\nsetp.ne.b32 p, %34, 0;\n"
        "wgmma.mma_async.sync.aligned.m64n64k16.f32.bf16.bf16 "
        "{%0,%1,%2,%3,%4,%5,%6,%7,%8,%9,%10,%11,%12,%13,%14,%15,%16,%17,%18,%19,%20,%21,%22,%23,%24,%25,%26,%27,%28,%29,%30,%31},"
        "%32, %33, p, 1, 1, 0, 1;\n}\n"
        : "+f"(d[0]), "+f"(d[1]), "+f"(d[2]), "+f"(d[3]), "+f"(d[4]), "+f"(d[5]), "+f"(d[6]), "+f"(d[7]),
          "+f"(d[8]), "+f"(d[9]), "+f"(d[10]), "+f"(d[11]), "+f"(d[12]), "+f"(d[13]), "+f"(d[14]), "+f"(d[15]),
          "+f"(d[16]), "+f"(d[17]), "+f"(d[18]), "+f"(d[19]), "+f"(d[20]), "+f"(d[21]), "+f"(d[22]), "+f"(d[23]),
          "+f"(d[24]), "+f"(d[25]), "+f"(d[26]), "+f"(d[27]), "+f"(d[28]), "+f"(d[29]), "+f"(d[30]), "+f"(d[31])
        : "l"(desc_a), "l"(desc_b), "r"(scale_d));
}
__device__ __forceinline__ uint64_t desc_kmajor(uint32_t tile16, int ks) {
    uint32_t lo = tile16 + ((ks >> 2) * 1024 + (ks & 3) * 2 + (1u << 16));
    return ((uint64_t)0x40000040u << 32) | lo;
}
__device__ __forceinline__ uint64_t desc_nmajor(uint32_t tile16, int ks) {
    uint32_t lo = tile16 + (ks * 128 + (1024u << 16));
    return ((uint64_t)0x40000040u << 32) | lo;
}
template <int TB>
__device__ __forceinline__ void mma_tile(float (&d)[64], const uint32_t* a, uint32_t tile16, int accumulate) {
#pragma unroll
    for (int ks = 0; ks < 8; ks++)
        wgmma_rs<TB>(d, a[4 * ks], a[4 * ks + 1], a[4 * ks + 2], a[4 * ks + 3],
                     TB ? desc_nmajor(tile16, ks) : desc_kmajor(tile16, ks), ks == 0 ? accumulate : 1);
    wg_commit();
}

template <int V> struct cint { static constexpr int value = V; };
#define GPF 126
#define XN 2
#define FINK 0
#define QAT 110
#define FSPLIT 4
#define SPLIT 16

#define TR(i)
#define TG(i)
#define PT(k)
#define TS(k)
#define TA(k)
#define TL(k)
#define TF(i)
#define TH(w, i)
#define TC(k)

__device__ __forceinline__ float silu_f(float v) { return v * rcp(1.f + ex2(v * -1.4426950408889634f)); }

__device__ __forceinline__ float inv_den(float var) {
    float r;
    asm("sqrt.approx.f32 %0, %1;" : "=f"(r) : "f"(bf_round(bf_round(var) + 1e-5f)));
    return rcp(bf_round(r));
}
__device__ __forceinline__ uint32_t normalise(uint32_t x2, uint32_t mm, float id) {
    const uint32_t d = bf2_sub(x2, mm);
    return pack_bf16(bf_lo(d) * id, bf_hi(d) * id);
}

__device__ __forceinline__ uint32_t silu2(uint32_t u) { return pack_bf16(silu_f(bf_lo(u)), silu_f(bf_hi(u))); }

__device__ __forceinline__ uint32_t silu2_ln(uint32_t u) {
    const float a = bf_lo(u), b = bf_hi(u);
    const float da = 1.f + ex2(a * -1.4426950408889634f), db = 1.f + ex2(b * -1.4426950408889634f);
    const float r = rcp(da * db);
    return pack_bf16(a * db * r, b * da * r);
}

__device__ __forceinline__ uint2 load_stat(Scratch* sc, int row) {
    uint2 v;
    asm volatile("ld.relaxed.gpu.global.v2.u32 {%0, %1}, [%2];" : "=r"(v.x), "=r"(v.y) : "l"(sc->stat + row) : "memory");
    return make_uint2(__byte_perm(v.x, 0, 0x1010), v.y);
}

constexpr int FSLOT = 6;
__device__ __forceinline__ void ffn_role(Scratch* sc, uint32_t ring, uint32_t ffull, uint32_t fempty, uint32_t alldone, int e, uint32_t ep, int warp,
                                         const __nv_bfloat16* __restrict__ x) {
    const uint32_t xs = ring + FSLOT * TILE_BYTES, hs = xs + 10 * 1024, cand = hs + 8 * 1024, sig = cand + 256;
    int tid;
    asm volatile("mov.u32 %0, %%tid.x;" : "=r"(tid));
    const int lane = tid & 31;
    [[maybe_unused]] const int wg = warp >> 2;
    const int nb = e == N_MOE - 1 ? 6 : 7, nkt = (nb + 1) >> 1;
    auto sync = [] { asm volatile("bar.sync 3, 256;" ::: "memory"); };
    if (tid < N_MOE) flag_wait(sc->flag_r + tid, ep);
    sync();
    TR(6);

    {
        uint32_t key[8];
#pragma unroll
        for (int i = 0; i < 8; i++) {
            const int j = warp * 256 + i * 32 + lane;
            const uint32_t u = __float_as_uint(__ldcg(sc->r + j) + 0.f);
            key[i] = (((u & 0x80000000u) ? ~u : (u | 0x80000000u)) & 0xffff0000u) | (uint32_t)(SEQ - j);
        }
#pragma unroll 1
        for (int k = 0; k < CAP; k++) {
            uint32_t b = key[0];
#pragma unroll
            for (int i = 1; i < 8; i++) b = max(b, key[i]);
            b = __reduce_max_sync(0xffffffffu, b);
#pragma unroll
            for (int i = 0; i < 8; i++) if (key[i] == b) key[i] = 0;
            if (lane == 0) asm volatile("st.shared.u32 [%0], %1;" ::"r"(cand + (warp * 8 + k) * 4), "r"(b) : "memory");
        }
    }
    sync();
    {
        uint32_t k0, k1, b = 0;
        asm volatile("ld.shared.v2.u32 {%0, %1}, [%2];" : "=r"(k0), "=r"(k1) : "r"(cand + lane * 8));
#pragma unroll 1
        for (int k = 0; k <= warp; k++) {
            b = __reduce_max_sync(0xffffffffu, max(k0, k1));
            if (k0 == b) k0 = 0;
            if (k1 == b) k1 = 0;
        }
        const int row = SEQ - (int)(b & 0xffffu);
        const uint2 st = load_stat(sc, row);
        uint4 v[3];
#pragma unroll
        for (int k = 0; k < 3; k++) v[k] = __ldg((const uint4*)(x + (size_t)row * DM) + min(lane + 32 * k, DM / 8 - 1));
#pragma unroll
        for (int k = 0; k < 3; k++) {
            const int i = lane + 32 * k;
            const float id = __uint_as_float(st.y);
            if (i < DM / 8)
                sts128(xs + (i >> 3) * 1024 + warp * 128 + (((i & 7) ^ warp) << 4), normalise(v[k].x, st.x, id), normalise(v[k].y, st.x, id),
                       normalise(v[k].z, st.x, id), normalise(v[k].w, st.x, id));
        }
        asm volatile("fence.proxy.async.shared::cta;" ::: "memory");
        if (lane == 0) {
            const float sg = bf_round(rcp(1.f + __expf(-__ldcg(sc->r + row))));
            asm volatile("st.shared.v2.b32 [%0], {%1, %2};" ::"r"(sig + warp * 8), "f"(sg), "r"(row) : "memory");
        }
    }
    sync();
    TR(7);

    {
        float acc[64];
        const int g = lane >> 2, t4 = lane & 3;
        auto block = [&](uint32_t a, uint32_t n, int step, int halves) {
#pragma unroll 1
            for (int i = 0; i < halves; i += 2, n += step) {
                const uint32_t s = n % FSLOT;
                mbar_wait(ffull + 8 * s, (n / FSLOT) & 1);
                const uint32_t a16 = (((a + i * 1024) & 0x3FFFFu) >> 4) | (1u << 16);
                const uint32_t b16 = ((ring + s * TILE_BYTES) & 0x3FFFFu) >> 4;
                auto mmas = [&](auto n_c) {
                    wg_fence();
#pragma unroll
                    for (int ks = 0; ks < decltype(n_c)::value; ks++)
                        wgmma_ss(acc, ((uint64_t)0x40000000u << 32) | (a16 + (ks >> 2) * 64 + (ks & 3) * 2), desc_nmajor(b16, ks), ks || i);
                    wg_commit();
                    wg_wait<0>();
                };
                if (i + 1 < halves) mmas(cint<8>());
                else mmas(cint<4>());
                if (lane == 0) mbar_arrive(fempty + 8 * s);
            }
            pin(acc);
        };
#pragma unroll 1
        for (int o = warp >> 2; o < nb; o += 2) {
            const bool pair = (o | 1) < nb;
            block(xs, 5 * (o & ~1) + (pair ? o & 1 : 0), pair ? 2 : 1, 10);
#pragma unroll
            for (int j = 0; j < 8; j++) {
                uint32_t h = pack_bf16(silu_f(bf_round(acc[4 * j])), silu_f(bf_round(acc[4 * j + 1])));
                asm("mul.rn.bf16x2 %0, %0, %1;" : "+r"(h) : "r"(pack_bf16(acc[32 + 4 * j], acc[33 + 4 * j])));
                asm volatile("st.shared.u32 [%0], %1;" ::"r"(hs + o * 1024 + g * 128 + ((j ^ g) << 4) + t4 * 4), "r"(h) : "memory");
            }
        }
        asm volatile("fence.proxy.async.shared::cta;" ::: "memory");
        sync();
        TR(8);
#pragma unroll 1
        for (int o = warp >> 2; o < 5; o += 2) {
            block(hs, 5 * nb + (o & ~1) * nkt + (o & 1), o < 4 ? 2 : 1, nb);
            if ((warp & 3) == 0) {
#pragma unroll
                for (int j = 0; j < 16; j++)
                    *(float2*)(sc->y + (e * CAP + g) * DM + o * 128 + j * 8 + t4 * 2) = make_float2(acc[4 * j], acc[4 * j + 1]);
            }
        }
    }
    sync();
    TR(9);
    if (tid == 0) flag_set(sc->flag_y + e, ep);
    if (tid < N_MOE) flag_wait(sc->flag_y + tid, ep);
    sync();
    if (lane == 0) mbar_arrive(alldone);
#pragma unroll 1
    for (int t = tid; t < 320; t += 256) {
        const int i = 2 * e * DM + t * 4;
        float4 y = __ldcg((const float4*)(sc->y + i));
#pragma unroll
        for (int j = 1; j < N_MOE; j++) {
            const float4 z = __ldcg((const float4*)(sc->y + j * CAP * DM + i));
            y.x += z.x; y.y += z.y; y.z += z.z; y.w += z.w;
        }
        float sg;
        int row;
        asm volatile("ld.shared.v2.b32 {%0, %1}, [%2];" : "=f"(sg), "=r"(row) : "r"(sig + (i / DM) * 8));
        const int o4 = (row * DM + i % DM) / 4;
        const uint2 v = __ldg((const uint2*)x + o4), st = load_stat(sc, row);
        uint32_t u0 = normalise(v.x, st.x, __uint_as_float(st.y)), u1 = normalise(v.y, st.x, __uint_as_float(st.y));
        asm("add.rn.bf16x2 %0, %0, %1;" : "+r"(u0) : "r"(pack_bf16(bf_round(y.x) * sg, bf_round(y.y) * sg)));
        asm("add.rn.bf16x2 %0, %0, %1;" : "+r"(u1) : "r"(pack_bf16(bf_round(y.z) * sg, bf_round(y.w) * sg)));
        sc->routed[i / 4] = make_uint2(silu2(u0), silu2(u1));
        if (i % DM == 0) sc->idx[i / DM] = row;
    }
    sync();
    TR(10);
    if (tid == 0) flag_set(sc->flag_u + e, ep);
}

__global__ void __launch_bounds__(384, 1)
fused_attn_kernel(const __nv_bfloat16* __restrict__ x, const __nv_bfloat16* __restrict__ wr,
                  __nv_bfloat16* __restrict__ out, Scratch* sc,
                  const __grid_constant__ CUtensorMap tm_x, const __grid_constant__ CUtensorMap tm_wq,
                  const __grid_constant__ CUtensorMap tm_k, const __grid_constant__ CUtensorMap tm_v,
                  const __grid_constant__ CUtensorMap tm_wo, const __grid_constant__ CUtensorMap tm_g,
                  const __grid_constant__ CUtensorMap tm_u, const __grid_constant__ CUtensorMap tm_d) {
    PT(0);
    extern __shared__ __align__(16) uint8_t smem_raw[];
    const uint32_t ring = smem_u32(smem_raw);
    const uint32_t stash = ring + NSLOT * TILE_BYTES;
    const uint32_t bars = stash + 3 * TILE_BYTES;
    const uint32_t full = bars, empty = bars + 32;
    const uint32_t xfull = bars + 64;
    const uint32_t rfull = bars + 144;
    const uint32_t rdone = bars + 288;
    const uint32_t vacant = bars + 336, routed = bars + 344, xgfull = bars + 352, gated = bars + 360;
    const uint32_t soon = bars + 376, qfull = bars + 384, epv = bars + 392, alldone = bars + 400;
    const uint32_t epoch = bars + 368;
    [[maybe_unused]] const uint32_t trbuf = bars + 416;
    const uint32_t ffull = rfull, fempty = rfull + 8 * FSLOT, qdone = rdone, h1done = rdone + 32, wperm = trbuf;

    const int warp = __shfl_sync(0xffffffffu, threadIdx.x >> 5, 0), wg = warp >> 2;
    const int rank = blockIdx.x & 1;
    const int cl = blockIdx.x >> 1;
    const int r7 = ((cl - 36) * 37) >> 8;
    const int qp = cl < 36 ? (cl < 4 ? 0 : (cl - 4) & 7) : cl - 35 - 7 * r7;
    const int grp = cl < 4 ? cl + 4 : cl < 36 ? (cl - 4) >> 3 : r7 + 4;
    const bool helper = blockIdx.x >= N_MAIN;
    const int qt = helper ? (blockIdx.x - N_MAIN) * 4 : qp * 2 + rank;

    auto load_x = [&](int w, int i, int tile) {
        const uint32_t bar = xfull + (w * 5 + i) * 8;
        mbar_expect_tx(bar, 16384);
        tma_3d(ring + (i == 4 ? 2 : 3 + i) * TILE_BYTES + w * 16384, &tm_x, bar, 0, tile * 128 + w * 64, i == 0 ? 8 : 2 * i - 2);
    };
    if (warp == 4) {
        if (elect_one()) {
#pragma unroll
            for (int i = 0; i < 10; i++) mbar_init(xfull + 8 * i, 1);
#pragma unroll
            for (int i = 0; i < XN; i++) load_x(i & 1, i >> 1, qt);
            asm volatile("fence.mbarrier_init.release.cluster;" ::: "memory");
        }
        __syncwarp();
    }
    PT(6);
    if ((ring & 0xFFFFFFu) != RING_OFFSET) return;
    PT(7);
    if (warp >= 5 && elect_one()) {
        if (warp == 5) {
#pragma unroll
            for (int i = 0; i < NSLOT; i++) { mbar_init(full + 8 * i, 1); mbar_init(empty + 8 * i, 16); }
            mbar_arrive(full + 16);
            mbar_arrive(full + 24);
        } else if (warp == 6) {
#pragma unroll
            for (int i = 0; i < 6; i++) mbar_init(rdone + 8 * i, helper ? 8 : 4);
        } else if (warp == 7) {
            mbar_init(vacant, 8); mbar_init(routed, 32); mbar_init(xgfull, 1); mbar_init(gated, 8); mbar_init(soon, 1);
            mbar_init(qfull, 1); mbar_init(epv, 1); mbar_init(alldone, 8);
        } else if (warp == 8) {
            asm volatile("prefetch.tensormap [%0];" ::"l"(&tm_wq) : "memory");
        } else {
#pragma unroll
            for (int i = 0; i < 6; i++) mbar_init(rfull + ((warp - 9) * 6 + i) * 8, helper && warp == 10 ? 4 : 1);
        }
        asm volatile("fence.mbarrier_init.release.cluster;" ::: "memory");
    }
    __syncwarp();
    PT(1);
    asm volatile("barrier.cluster.arrive.relaxed.aligned;" ::: "memory");
    if (warp == 4) {
        if (elect_one()) {
#pragma unroll
            for (int i = XN; i < 10; i++) load_x(i & 1, i >> 1, qt);
        }
        __syncwarp();
    }

    if (wg == 2) {
        asm volatile("setmaxnreg.dec.sync.aligned.u32 24;");
        asm volatile("barrier.cluster.wait.aligned;" ::: "memory");
        uint32_t lane;
        asm volatile("mov.u32 %0, %%laneid;" : "=r"(lane));
        PT(2);
        if (warp == 8 && helper) {
          if (elect_one()) {
#pragma unroll 1
            for (int t = 0; t < 4; t++) {
#pragma unroll 1
                for (int i = 0; i < 20; i++) {
                    const int s = i % 3;
                    mbar_wait(empty + 8 * s, ((t + (i + 1) / 3) & 1) ^ 1);
                    mbar_expect_tx(full + 8 * s, TILE_BYTES);
                    tma_2d_mc(ring + s * TILE_BYTES + rank * 16384, &tm_wq, full + 8 * s, (((i / 5) * 2 + rank) * 4 + 3) * 128 + 64,
                              ((i + 4) % 5) * 128);
                    if (t == 0 && i == 2) {
                        asm volatile("nanosleep.u32 1500;");
#pragma unroll 1
                        for (int k = 3 + ((blockIdx.x >> 1) & 1); k < 20; k += 2) tma_prefetch(&tm_wq, (((k / 5) * 2 + rank) * 4 + 3) * 128 + 64, ((k + 4) % 5) * 128);
                    }
                    if (i == 2 && t < 3) {
#pragma unroll 1
                        for (int k = 2; k < 8; k++) load_x(k & 1, k >> 1, qt + t + 1);
                    }
                    if (i == 18 && t < 3) {
                        mbar_wait(empty + 24, t & 1);
                        load_x(0, 0, qt + t + 1); load_x(1, 0, qt + t + 1);
                    }
                }
                if (t < 3) {
                    mbar_wait(empty + 16, t & 1);
                    mbar_arrive(full + 16);
                    load_x(0, 4, qt + t + 1); load_x(1, 4, qt + t + 1);
                }
            }
            const int e = blockIdx.x - N_MAIN, nb = e == N_MOE - 1 ? 6 : 7, nkt = (nb + 1) >> 1;
            mbar_wait(h1done, 0);
            uint32_t s = 0, ph = 1;
#pragma unroll 1
            for (int o0 = 0, w; o0 < nb + 5; o0 += w) {
                const bool up = o0 < nb;
                w = o0 + 1 < (up ? nb : nb + 5) ? 2 : 1;
#pragma unroll 1
                for (int k = 0; k < (up ? 5 : nkt) * w; k++) {
                    const int o = o0 + (k & (w - 1)), i = k >> (w - 1);
                    mbar_wait(fempty + 8 * s, ph);
                    mbar_expect_tx(ffull + 8 * s, TILE_BYTES);
                    const int c0 = up ? (e * 7 + o) * 64 : (o - nb) * 128, c1 = (up ? 0 : e * 448) + i * 128;
                    tma_2d(ring + s * TILE_BYTES, up ? &tm_g : &tm_d, ffull + 8 * s, c0, c1);
                    tma_2d(ring + s * TILE_BYTES + 16384, up ? &tm_u : &tm_d, ffull + 8 * s, up ? c0 : c0 + 64, c1);
                    if (++s == FSLOT) { s = 0; ph ^= 1; }
                }
            }
          }
        } else if (warp == 8) {
          if (elect_one()) {
            PT(3);
            auto coords = [&](int i, const CUtensorMap*& tm, int& c0, int& c1) {
                c0 = rank * 64;
                if (i < 20) {
                    const int ps = i / 5;
                    tm = &tm_wq; c1 = (i % 5 < 3 ? i % 5 : 7 - i % 5) * 128;
                    if (ps == 1) {
                        c0 = 0;
                        c1 = (i == 5 ? rank : i == 6 ? 2 : 4 - rank) * 128;
                    }
                    c0 += (grp * 4 + (ps < 2 ? 2 + ps : 3 - ps)) * 128;
                } else if (i < 148) {
                    const int u = i - 20;
                    const bool isk = (u == 0) || ((u & 1) && u != 127);
                    const int b = isk ? (u + 1) >> 1 : (u == 127 ? 63 : (u >> 1) - 1);
                    tm = isk ? &tm_k : &tm_v; c1 = (grp * 64 + b) * 128;
                } else {
                    tm = &tm_wo; c0 = (i < 152 ? ((i - 132) >> 1) ^ (grp >> 2) : (grp + ((i - 150) >> 1)) & 7) * 64; c1 = (grp * 4 + (i & 1) * 2 + rank) * 128;
                }
            };
#pragma unroll 1
            for (int i = 0; i < 168; i++) {
                const CUtensorMap* tm;
                int c0, c1;
                if (i == 8) i = 10;
                const int a = i < 8 ? i : i - 2;
                const int s = i < 20 ? a % 3 : (i & 3);
                const uint32_t ph = i < 20 ? ((a + 1) / 3) & 1 : ((i >> 2) & 1) ^ (s < 2);
                coords(i, tm, c0, c1);
                if (i == QAT) mbar_wait(qfull, 0);
                mbar_wait(empty + 8 * s, ph ^ 1);
                if (i == 6) {
                    mbar_expect_tx(full + 8 * s, TILE_BYTES / 2);
                    if (rank == 0) tma_2d_mc(ring + s * TILE_BYTES, tm, full + 8 * s, c0, c1);
                } else {
                    mbar_expect_tx(full + 8 * s, TILE_BYTES);
                    tma_2d_mc(ring + s * TILE_BYTES + rank * 16384, tm, full + 8 * s, c0, c1);
                }
                if (i == 140) mbar_arrive(soon);
                if (i >= 163 && i < 167) {
                    if (i == 163) {
                        TL(0);
                        mbar_wait(routed, 0);
                        asm volatile("fence.proxy.async.global;" ::: "memory");
                        TL(1);
                        mbar_expect_tx(xgfull, TILE_BYTES);
                    }
                    asm volatile("cp.async.bulk.shared::cluster.global.mbarrier::complete_tx::bytes [%0], [%1], 8192, [%2];"
                                 ::"r"(stash + 3 * 16384 + (i - 163) * 8192), "l"(sc->gate + blockIdx.x * 2560 + (i - 163) * 512), "r"(xgfull) : "memory");
                }
                if (i == 12) asm volatile("prefetch.tensormap [%0];\nprefetch.tensormap [%1];" ::"l"(&tm_k), "l"(&tm_v) : "memory");
                if (i == 140) asm volatile("prefetch.tensormap [%0];" ::"l"(&tm_wo) : "memory");
                if (i >= GPF && i < GPF + 10)
                    asm volatile("cp.async.bulk.prefetch.L2.global [%0], 4096;" ::"l"(sc->gate + blockIdx.x * 2560 + (i - GPF) * 256) : "memory");
                const int j = i < 2 ? 2 + i : i == 2 ? 4 + ((qp - 4) & 7) : i + 9;
                if (j < 168 && (j & 7) == qp && (j & ~1) != 8) {
                    coords(j, tm, c0, c1);
                    tma_prefetch(tm, c0, c1);
                }
            }
            sc->epoch[blockIdx.x] += 1;
          }
        } else if (warp == 9) {
            const uint32_t ep = sc->epoch[blockIdx.x] + 1;
            if (helper) {
#pragma unroll 1
                for (int t = 0; t < 4; t++) {
                    if (t == 3) {
                        mbar_wait_sleep(qdone + 40, 0);
                        if (lane == 0) flag_set(sc->flag_r + (blockIdx.x - N_MAIN), ep);
                    }
                    mbar_wait_sleep(qdone + 8 * t, 0);
                    if (lane == 0) flag_set(sc->flag_q + qt + t, ep);
                }
                if (lane == 0) sc->epoch[blockIdx.x] = ep;
            } else {
                mbar_wait_sleep(gated, 0);
                flag_wait_bounded<300>(sc->flag_q + qt, ep);
                asm volatile("fence.proxy.async.global;" ::: "memory");
                if (lane == 0) mbar_expect_tx(qfull, 16384);
                __syncwarp();
                if (lane < 8)
                    asm volatile("cp.async.bulk.shared::cluster.global.mbarrier::complete_tx::bytes [%0], [%1], 2048, [%2];"
                                 ::"r"(stash + 2 * TILE_BYTES + lane * 4096 + 2048),
                                   "l"(sc->qoff + ((qt * 4 + (grp >> 1)) * 8 + lane) * 256 + (grp & 1) * 128), "r"(qfull) : "memory");
            }
            mbar_wait_bounded(alldone, 0);
        } else if (helper) {
        } else if (warp == 10) {
            const uint32_t ep = sc->epoch[blockIdx.x] + 1;
            if (lane == 0) {
                asm volatile("st.shared.u32 [%0], %1;" ::"r"(epoch), "r"(ep) : "memory");
                mbar_arrive(epv);
            }
            mbar_wait_sleep(gated, 0);
            flag_wait<400>(sc->flag_u + (lane & 3), ep);
            __syncwarp();
            const int rrow = __ldcg(sc->idx + (lane & 7));
            uint32_t hit = __ballot_sync(0xffffffffu, lane < 8 && (rrow >> 7) == qt);
            while (hit) {
                const int k = __ffs(hit) - 1, row = __shfl_sync(0xffffffffu, rrow, k);
                hit &= hit - 1;
#pragma unroll 1
                for (int i = lane; i < 40; i += 32) {
                    const int th = ((row >> 4) & 7) * 32 + (row & 7) * 4 + (i & 3);
                    ((uint32_t*)sc->gate)[(((blockIdx.x * 5 + (i >> 3)) * 2 + 1) * 256 + th) * 4 + ((i >> 1) & 2) + ((row >> 3) & 1)] =
                        __ldcg((const uint32_t*)sc->routed + k * (DM / 2) + (i < 32 ? grp * 32 + i : 224 + grp * 8 + i));
                }
            }
            mbar_arrive(routed);
        } else if (warp == 11) {
            const uint32_t ep = sc->epoch[blockIdx.x] + 1;
            const uint32_t unit = lane < 16 ? lane >> 3 : (lane >> 1) - 6;
            const uint32_t ofs = (lane & 1) * 8192 + (lane < 16 ? ((lane >> 1) & 3) * 2048 : 0);
            if (lane < 18) mbar_expect_tx(rfull + 8 * lane, 8192);
            mbar_wait_sleep(soon, 0);
            uint32_t done = lane >= 30;
            do {
                if (!done) {
                    uint4 v;
                    asm volatile("ld.relaxed.gpu.global.v4.u32 {%0, %1, %2, %3}, [%4];" : "=r"(v.x), "=r"(v.y), "=r"(v.z), "=r"(v.w)
                                 : "l"(sc->flag + (qt * 8 + grp) * 32 + lane) : "memory");
                    uint32_t ok = v.x == ep && v.y == ep && v.z == ep && v.w == ep;
                    if (ok)
                        asm volatile("{\n.reg .pred p;\nmbarrier.test_wait.parity.shared::cta.b64 p, [%1], 0;\nselp.u32 %0, 1, 0, p;\n}\n"
                                     : "=r"(ok) : "r"(unit >= 6 ? rdone + (lane - 24) * 8 : vacant) : "memory");
                    done = ok;
                    if (ok)
                        asm volatile("cp.async.bulk.shared::cluster.global.mbarrier::complete_tx::bytes [%0], [%1], %2, [%3];"
                                     ::"r"(stash + (unit >= 6 ? unit - 6 : unit) * 16384 + ofs),
                                       "l"((const char*)sc->part + ((qt * 8 + grp) * 9 + unit) * 16384 + ofs), "r"(lane < 16 ? 2048 : 8192),
                                       "r"(rfull + 16 * unit + 8 * (lane & 1)) : "memory");
                }
            } while (!__all_sync(0xffffffffu, done));
        }
    } else {
        asm volatile("setmaxnreg.inc.sync.aligned.u32 240;");
        const uint32_t lane = threadIdx.x & 31;
        PT(2);
        asm volatile("barrier.cluster.wait.aligned;" ::: "memory");
        PT(3);
        const int my_bar = 1 + wg, other_bar = 2 - wg;
        const uint32_t my_stash = stash + warp * 4096 + lane * 16;
        constexpr uint32_t T16 = TILE_BYTES / 16;
        constexpr uint32_t ring16 = RING_OFFSET >> 4;
        uint32_t rel = 0;
        if (lane < 2)
            asm("mapa.shared::cluster.u32 %0, %1, %2;" : "=r"(rel) : "r"(empty), "r"(lane));
        rel = opaque(rel);

        const int zero = gridDim.y - 1;
        PT(4);

        uint32_t q[32];
        float acc[64];
        float wsum;
        uint32_t ep_tag;
        uint2 st0, st1;
        auto project = [&](auto helper_c, int job) {
            constexpr bool HELPER = decltype(helper_c)::value;
            float (&acc32)[32] = *reinterpret_cast<float (*)[32]>(&acc[0]);
            const int tile = qt + job;
            uint32_t lane = threadIdx.x & 31;
            if (HELPER) asm volatile("mov.u32 %0, %%laneid;" : "=r"(lane));
            uint32_t xa[128];
            const uint32_t lm_off = wg * 16384 + ((warp & 3) * 16 + (lane & 15)) * 128 + (((lane >> 4) ^ (lane & 7)) << 4);
            float sm[4][4] = {}, sq[4][4] = {};
            constexpr uint32_t ONES = 0x3f803f80u;
            constexpr float SC = 0.08838834764831845f * 1.4426950408889634f;
            auto squares = [&](const uint32_t* a) {
#pragma unroll
                for (int r = 0; r < 4; r++) hmma8(sq[r], a[r & 2], a[(r & 2) + 1], a[r]);
            };
            const int row = tile * 128 + warp * 16 + (lane >> 2);
            auto load_stats = [&](int t) {
                asm volatile("ld.relaxed.gpu.global.v2.u32 {%0, %1}, [%4];\nld.relaxed.gpu.global.v2.u32 {%2, %3}, [%4 + 64];"
                             : "=r"(st0.x), "=r"(st0.y), "=r"(st1.x), "=r"(st1.y) : "l"(sc->stat + t * 128 + warp * 16 + (lane >> 2)) : "memory");
            };
            uint32_t mm0, mm1;
            float rd0, rd1;
            if (HELPER && job == 0) load_stats(tile);
#pragma unroll
            for (int i = 0; i < 5; i++) {
                mbar_wait(xfull + (wg * 5 + i) * 8, HELPER ? job & 1 : 0);
                if (i == 0) PT(5);
                if (HELPER && i == 0) TR(20 + job * 8);
                if (HELPER && i == 4) TR(20 + job * 8 + 7);
                if (HELPER && job == 1) TR(110 + i);
                const uint32_t base = ring + (i == 4 ? 2 : 3 + i) * TILE_BYTES + lm_off;
                uint32_t* a = xa + (i == 0 ? 96 : 32 * (i - 1));
#pragma unroll
                for (int ks = 0; ks < 8; ks++)
                    ldsm4((base ^ ((ks & 3) << 5)) + (ks >> 2) * 8192, a[4 * ks], a[4 * ks + 1], a[4 * ks + 2], a[4 * ks + 3]);
                if (i == 4) PT(9);
                uint32_t wb[16];
#pragma unroll
                for (int ks = 0; ks < 8; ks++) {
                    wb[2 * ks] = ONES; wb[2 * ks + 1] = ONES;
                    if (HELPER)
                        asm volatile("ld.shared.v2.u32 {%0, %1}, [%2];" : "=r"(wb[2 * ks]), "=r"(wb[2 * ks + 1]) : "r"(wperm + (lane & 3) * 8 + ((i == 0 ? 32 : 8 * i - 8) + ks) * 32));
                }
#pragma unroll
                for (int ks = 0; ks < 8; ks++) {
                    hmma(sm[ks & 3], a[4 * ks], a[4 * ks + 1], a[4 * ks + 2], a[4 * ks + 3], wb[2 * ks], wb[2 * ks + 1]);
                    if (!HELPER && i < 4) squares(a + 4 * ks);
                }
                if (HELPER && i == 0) {
                    while (__any_sync(0xffffffffu, ((st0.x ^ ep_tag) | (st1.x ^ ep_tag)) >> 16)) load_stats(tile);
                    mm0 = __byte_perm(st0.x, 0, 0x1010); mm1 = __byte_perm(st1.x, 0, 0x1010);
#pragma unroll
                    for (int ks = 0; ks < 8; ks++)
                        stsm4((base ^ ((ks & 3) << 5)) + (ks >> 2) * 8192, bf2_sub(a[4 * ks], mm0), bf2_sub(a[4 * ks + 1], mm1),
                              bf2_sub(a[4 * ks + 2], mm0), bf2_sub(a[4 * ks + 3], mm1));
                    asm volatile("fence.proxy.async.shared::cta;" ::: "memory");
                }
            }
            release_at<16>(rel);
            sched_fence(zero);
            const float m0 = ((sm[0][0] + sm[1][0]) + (sm[2][0] + sm[3][0])) * (HELPER ? 1.f : 1.f / DM);
            const float m1 = ((sm[0][2] + sm[1][2]) + (sm[2][2] + sm[3][2])) * (HELPER ? 1.f : 1.f / DM);
            if (HELPER) {
                const float id0 = __uint_as_float(st0.y), id1 = __uint_as_float(st1.y);
                rd0 = SC * id0; rd1 = SC * id1;
                if ((lane & 3) == 0) {
                    sc->r[row] = bf_round((m0 - bf_lo(mm0) * wsum) * id0);
                    sc->r[row + 8] = bf_round((m1 - bf_lo(mm1) * wsum) * id1);
                }
                __syncwarp();
                if (job == 3 && lane == 0) mbar_arrive(qdone + 40);
            } else {
                mm0 = pack_bf16(m0, m0); mm1 = pack_bf16(m1, m1);
            }
            auto centre = [&](int kt) {
#pragma unroll
                for (int i = 32 * kt; i < 32 * kt + 32; i++) asm volatile("sub.rn.bf16x2 %0, %0, %1;" : "+r"(xa[i]) : "r"((i & 1) ? mm1 : mm0));
            };
            if (!HELPER) {
#pragma unroll
                for (int ks = 0; ks < 8; ks++) squares(xa + 96 + 4 * ks);
            }
            if (!HELPER) centre(0);
            if (wg == 1) bar_arrive(1);
            auto diag = [&](int r, int h) { return (lane & 4) ? sq[r][h + 1] + sq[r + 2][h + 1] : sq[r][h] + sq[r + 2][h]; };
            auto spread = [&](float v) { return __shfl_sync(0xffffffffu, v, (lane & ~3u) | (lane >> 3)) * (1.f / DM); };
            if (!HELPER) { rd0 = diag(0, 0); rd1 = diag(1, 2); }
            PT(10);

            if (HELPER) TR(20 + job * 8 + 1);
            uint32_t qs = 0, qph = HELPER ? job & 1 : 0;
            uint4 gx;
            if (HELPER) {
#pragma unroll
                for (int i = 0; i < 64; i++) acc[i] = 0.f;
            }
            const uint32_t xs16 = ring16 + 3 * T16 + wg * 1024;
            constexpr int SS = HELPER ? 0 : 3;
            auto finish_stats = [&] {
                float v0 = spread(rd0) - m0 * m0, v1 = spread(rd1) - m1 * m1;
                if (__any_sync(0xffffffffu, !(m0 * m0 <= 256.f * v0 && m1 * m1 <= 256.f * v1))) {
                    const uint4* xr = (const uint4*)x + row * (DM / 8) + (lane & 3);
                    v0 = 0.f; v1 = 0.f;
#pragma unroll 1
                    for (int i = 0; i < DM / 32; i++) {
                        const uint4 a = __ldg(xr + 4 * i), b = __ldg(xr + DM + 4 * i);
                        const uint32_t w[8] = {a.x, a.y, a.z, a.w, b.x, b.y, b.z, b.w};
#pragma unroll
                        for (int k = 0; k < 8; k++) {
                            const uint32_t d = bf2_sub(w[k], k < 4 ? mm0 : mm1);
                            float& v = k < 4 ? v0 : v1;
                            v = fmaf(bf_lo(d), bf_lo(d), fmaf(bf_hi(d), bf_hi(d), v));
                        }
                    }
#pragma unroll
                    for (int d = 1; d <= 2; d <<= 1) { v0 += __shfl_xor_sync(0xffffffffu, v0, d); v1 += __shfl_xor_sync(0xffffffffu, v1, d); }
                    v0 *= 1.f / DM; v1 *= 1.f / DM;
                    const float e0 = m0 - bf_lo(mm0), e1 = m1 - bf_lo(mm1);
                    v0 -= e0 * e0; v1 -= e1 * e1;
                }
                const float id0 = inv_den(fmaxf(v0, 0.f)), id1 = inv_den(fmaxf(v1, 0.f));
                rd0 = SC * id0; rd1 = SC * id1;
                if (warp == grp) {
                    mbar_wait(epv, 0);
                    uint32_t tg;
                    asm volatile("ld.shared.u32 %0, [%1];" : "=r"(tg) : "r"(epoch));
                    if ((lane & 3) == 0)
                        asm volatile("st.relaxed.gpu.global.v2.u32 [%0], {%1, %2};\nst.relaxed.gpu.global.v2.u32 [%0 + 64], {%3, %4};"
                                     ::"l"(sc->stat + row), "r"(__byte_perm(mm0, tg, 0x5410)), "f"(id0), "r"(__byte_perm(mm1, tg, 0x5410)), "f"(id1) : "memory");
                }
            };
#pragma unroll 1
            for (int pass = 0;; pass++) {
                const uint32_t hs = my_stash + (pass == 2 ? 0 : pass + 1) * TILE_BYTES;
                uint4* const dst = sc->qoff + ((tile * 4 + pass) * 8 + warp) * 256 + lane;
                auto put = [&](int lo) {
#pragma unroll
                    for (int i = lo; i < lo + 4; i++) {
                        const uint4 v = make_uint4(pack_bf16(acc[8 * i] * rd0, acc[8 * i + 1] * rd0), pack_bf16(acc[8 * i + 2] * rd1, acc[8 * i + 3] * rd1),
                                                   pack_bf16(acc[8 * i + 4] * rd0, acc[8 * i + 5] * rd0), pack_bf16(acc[8 * i + 6] * rd1, acc[8 * i + 7] * rd1));
                        if (HELPER) dst[i * 32] = v;
                        else sts128(hs + i * 512, v.x, v.y, v.z, v.w);
                        if (i == 2 || i == 5) sched_fence(zero);
                    }
                };
                auto gate_load = [&](int j) {
                    const uint32_t* src = (const uint32_t*)x + (qt * 128 + warp * 16 + (lane >> 2)) * (DM / 2) + (lane & 3) +
                                          (j < 4 ? grp * 32 + j * 8 : 256 + grp * 8);
                    asm volatile("ld.global.nc.u32 %0, [%4];\nld.global.nc.u32 %1, [%4 + %5];\n"
                                 "ld.global.nc.u32 %2, [%4 + 16];\nld.global.nc.u32 %3, [%4 + %5 + 16];"
                                 : "=r"(gx.x), "=r"(gx.y), "=r"(gx.z), "=r"(gx.w) : "l"(src), "n"(8 * DM * 2));
                };
                auto gate_store = [&](int j) {
                    const float id0 = rd0 * (1.f / SC), id1 = rd1 * (1.f / SC);
                    uint4* g = sc->gate + (blockIdx.x * 5 + j) * 512 + threadIdx.x;
                    g[0] = gx;
                    g[256] = make_uint4(silu2_ln(normalise(gx.x, mm0, id0)), silu2_ln(normalise(gx.y, mm1, id1)),
                                        silu2_ln(normalise(gx.z, mm0, id0)), silu2_ln(normalise(gx.w, mm1, id1)));
                };
                auto advance = [&] {
                    const uint32_t r = rel ? rel + 8 * qs : 0;
                    if (++qs == 2) qph ^= 1;
                    if (qs == 3) qs = 0;
                    return r;
                };
                if (!HELPER && pass == 1) {
#pragma unroll
                    for (int turn = 0; turn < 3; turn++) {
                        if (turn) mbar_wait(full + 8 * qs, qph);
                        bar_sync(my_bar);
                        const uint32_t tile16 = ring16 + qs * T16;
                        wg_fence();
#pragma unroll
                        for (int ks = 0; ks < (turn == 1 ? 8 : 16); ks++) {
                            const uint32_t* a = xa + (turn == 2 ? 64 : turn * 64) + 4 * ks;
                            if (turn == 2 && ks < 8) wgmma_ss64(acc32, desc_kmajor(xs16 - (ks >> 2) * 512, ks), desc_nmajor(tile16, ks), 1);
                            else wgmma_rs64(acc32, a[0], a[1], a[2], a[3], desc_nmajor(tile16, ks), turn || ks);
                        }
                        wg_commit();
                        bar_arrive(other_bar);
                        const uint32_t rl = advance();
                        if (turn == 2) mbar_wait(full + 8 * qs, qph);
                        wg_wait<0>();
                        TA(5 + 2 * turn);
                        release_at<0>(rl);
                    }
                    pin(acc32);
                    put(0);
                    continue;
                }
                uint32_t rl = 0;
#pragma unroll
                for (int kt = 0; kt < 5; kt++) {
                    const bool takes = !HELPER || kt == 0 || kt == 2 || kt == 3, passes = !HELPER || kt == 1 || kt == 2 || kt == 4;
                    if (kt != 0 || pass == 0) mbar_wait(full + 8 * qs, qph);
                    if (takes) bar_sync(my_bar);
                    const uint32_t tile16 = ring16 + qs * T16;
                    wg_fence();
                    if (kt != SS) {
                        mma_tile<1>(acc, xa + (kt < SS ? kt : kt - 1) * 32, tile16, kt != 0);
                    } else {
#pragma unroll
                        for (int ks = 0; ks < 8; ks++) wgmma_ss(acc, desc_kmajor(xs16 - (ks >> 2) * 512, ks), desc_nmajor(tile16, ks), kt || ks);
                        wg_commit();
                    }
                    if (passes && !(HELPER && kt == 4 && pass == 3 && wg == 1)) bar_arrive(other_bar);
                    if (HELPER && pass == 0 && kt < 4) centre(kt);
                    if (!HELPER && pass == 0 && kt < 3) {
#pragma unroll
                        for (int ks = 3 * kt; ks < 3 * kt + 3 && ks < 8; ks++) {
                            const uint32_t ad = ((ring + 3 * TILE_BYTES + lm_off) ^ ((ks & 3) << 5)) + (ks >> 2) * 8192;
                            uint32_t a, b, c, d;
                            ldsm4(ad, a, b, c, d);
                            stsm4(ad, bf2_sub(a, mm0), bf2_sub(b, mm1), bf2_sub(c, mm0), bf2_sub(d, mm1));
                        }
                        if (kt == 2) asm volatile("fence.proxy.async.shared::cta;" ::: "memory");
                    }
                    if (!HELPER && pass == 0 && kt == FINK) finish_stats();
                    if (HELPER && kt == 2 && pass == 3 && job < 3) load_stats(tile + 1);
                    if (!HELPER && pass >= 2 && kt < 4) {
                        if (kt & 1) gate_store((pass - 2) * 2 + (kt >> 1));
                        else gate_load((pass - 2) * 2 + (kt >> 1));
                    }
                    if (!HELPER && pass == 2 && kt == 3) gate_load(4);
                    if (!HELPER && pass == 2 && kt == 4) gate_store(4);
                    const uint32_t rl_prev = rl;
                    rl = advance();
                    if (!passes) continue;
                    if (HELPER && kt != 2) {
                        wg_wait<1>();
                        if (job == 1) TR(120 + pass * 5 + kt - 1);
                        release_at<0>(rl_prev);
                        if (kt == 1 && pass == 3) release_at<24>(rel);
                    }
                    if (kt == 4 && !(HELPER && pass == 3)) mbar_wait(full + 8 * qs, qph);
                    wg_wait<0>();
                    if (!HELPER) TA(pass * 5 + kt);
                    if (HELPER && job == 1) TR(120 + pass * 5 + kt);
                    release_at<0>(rl);
                    if (!HELPER && kt < 3 && pass == 0) centre(kt + 1);
                }
                pin(acc);
                if (!HELPER && pass == 3) break;
                put(0);
                put(4);
                if (HELPER) TR(20 + job * 8 + 2 + pass);
                if (HELPER && pass == 3) {
                    __syncwarp();
                    if (lane == 0) mbar_arrive(qdone + 8 * job);
                    return;
                }
            }
            release_at<24>(rel);
            if (lane == 0) mbar_arrive(gated);
#pragma unroll
            for (int i = 0; i < 32; i++) {
                const float r = (i & 1) ? rd1 : rd0;
                q[i] = pack_bf16(acc[2 * i] * r, acc[2 * i + 1] * r);
            }
        };
        if (helper) {
            const uint32_t ep = sc->epoch[blockIdx.x] + 1;
            if (threadIdx.x < 160) {
                const uint32_t* w32 = (const uint32_t*)wr + (threadIdx.x >> 2) * 8 + (threadIdx.x & 3);
                asm volatile("st.shared.v2.u32 [%0], {%1, %2};" ::"r"(wperm + threadIdx.x * 8), "r"(__ldg(w32)), "r"(__ldg(w32 + 4)) : "memory");
            }
            asm volatile("bar.sync 3, 256;" ::: "memory");
            float ws[4] = {};
#pragma unroll 4
            for (int ks = 0; ks < 40; ks++) {
                uint32_t b0, b1;
                asm volatile("ld.shared.v2.u32 {%0, %1}, [%2];" : "=r"(b0), "=r"(b1) : "r"(wperm + (lane & 3) * 8 + ks * 32));
                hmma(ws, 0x3f803f80u, 0x3f803f80u, 0x3f803f80u, 0x3f803f80u, b0, b1);
            }
            wsum = ws[0];
            ep_tag = ep << 16;
            TR(0);
#pragma unroll 1
            for (int job = 0; job < 4; job++) {
                project(cint<1>(), job);
                TR(1 + job);
            }
            if (elect_one()) mbar_arrive(h1done);
            ffn_role(sc, ring, ffull, fempty, alldone, blockIdx.x - N_MAIN, ep, warp, x);
            return;
        }
        project(cint<0>(), 0);
        TR(2);
        TG(112);

        float o[64];
        uint32_t p[32];
        float l0, l1;
        constexpr float L_LO = 9.313225746154785e-10f, L_HI = 1.152921504606847e18f;
        float l_hi = L_HI;
        float (&s)[64] = acc;

        auto exp_range = [&](const float (&s)[64], int lo, int hi, float& u0, float& u1) {
            float w0 = 0.f, w1 = 0.f;
#pragma unroll
            for (int i = lo; i < hi; i += 4) {
                const float e0 = ex2(s[i]), e1 = ex2(s[i + 1]), e2 = ex2(s[i + 2]), e3 = ex2(s[i + 3]);
                u0 += e0; u1 += e2;
                if (i == lo) { w0 = e1; w1 = e3; } else { w0 += e1; w1 += e3; }
                p[i / 2] = pack_bf16(e0, e1); p[i / 2 + 1] = pack_bf16(e2, e3);
            }
            u0 += w0; u1 += w1;
        };
        auto unsafe = [&](bool first, float u0, float u1) {
            return (bool)__any_sync(0xffffffffu, !(u0 + u1 <= l_hi) || (first && !(fminf(u0, u1) >= L_LO)));
        };
        auto softmax_true_max = [&](const float (&s)[64], bool first, float b0, float b1, float& u0, float& u1) {
            uint32_t t;
            asm volatile("mov.u32 %0, %%tid.x;" : "=r"(t));
            uint4* const st = sc->rare + blockIdx.x * (17 * 256) + t;
            auto ld = [](const uint4* a) {
                uint4 v;
                asm volatile("ld.global.v4.u32 {%0, %1, %2, %3}, [%4];" : "=r"(v.x), "=r"(v.y), "=r"(v.z), "=r"(v.w) : "l"(a) : "memory");
                return v;
            };
#pragma unroll
            for (int i = 0; i < 16; i++)
                asm volatile("st.global.v4.f32 [%0], {%1, %2, %3, %4};" ::"l"(st + i * 256), "f"(s[4 * i]), "f"(s[4 * i + 1]), "f"(s[4 * i + 2]), "f"(s[4 * i + 3]) : "memory");
            float a0 = s[0], a1 = s[2];
#pragma unroll 1
            for (int i = 0; i < 16; i++) {
                const uint4 v = ld(st + i * 256);
                a0 = fmaxf(a0, fmaxf(__uint_as_float(v.x), __uint_as_float(v.y)));
                a1 = fmaxf(a1, fmaxf(__uint_as_float(v.z), __uint_as_float(v.w)));
            }
            float t0 = b0, t1 = b1, sg0 = 0.f, sg1 = 0.f;
            if (l_hi < 0.f) {
                const uint4 v = ld(st + 16 * 256);
                sg0 = __uint_as_float(v.x); sg1 = __uint_as_float(v.y);
            }
#pragma unroll
            for (int d = 1; d <= 2; d <<= 1) {
                a0 = fmaxf(a0, __shfl_xor_sync(0xffffffffu, a0, d)); a1 = fmaxf(a1, __shfl_xor_sync(0xffffffffu, a1, d));
                t0 += __shfl_xor_sync(0xffffffffu, t0, d); t1 += __shfl_xor_sync(0xffffffffu, t1, d);
            }
            if (!first) {
                a0 = fmaxf(a0, l_hi < 0.f ? sg0 : __log2f(t0)); a1 = fmaxf(a1, l_hi < 0.f ? sg1 : __log2f(t1));
            }
            const float al0 = first ? 1.f : ex2(sg0 - a0), al1 = first ? 1.f : ex2(sg1 - a1);
            asm volatile("st.global.v2.f32 [%0], {%1, %2};" ::"l"(st + 16 * 256), "f"(a0), "f"(a1) : "memory");
            l_hi = -1.f;
            u0 = b0 * al0; u1 = b1 * al1;
#pragma unroll 1
            for (int i = 0; i < 16; i++) {
                const uint4 v = ld(st + i * 256);
                const float e0 = ex2(__uint_as_float(v.x) - a0), e1 = ex2(__uint_as_float(v.y) - a0);
                const float e2 = ex2(__uint_as_float(v.z) - a1), e3 = ex2(__uint_as_float(v.w) - a1);
                u0 += e0 + e1; u1 += e2 + e3;
                asm volatile("st.global.v2.u32 [%0], {%1, %2};" ::"l"((uint2*)(st + (i >> 1) * 256) + (i & 1)), "r"(pack_bf16(e0, e1)), "r"(pack_bf16(e2, e3)) : "memory");
            }
#pragma unroll
            for (int i = 0; i < 8; i++) {
                const uint4 v = ld(st + i * 256);
                p[4 * i] = v.x; p[4 * i + 1] = v.y; p[4 * i + 2] = v.z; p[4 * i + 3] = v.w;
            }
            if (&s != &o) {
#pragma unroll
                for (int i = 0; i < 64; i++) o[i] *= (i & 2) ? al1 : al0;
            }
        };
        auto inv_sums = [&](float& i0, float& i1) {
            float a = l0, b = l1;
            a += __shfl_xor_sync(0xffffffffu, a, 1); b += __shfl_xor_sync(0xffffffffu, b, 1);
            a += __shfl_xor_sync(0xffffffffu, a, 2); b += __shfl_xor_sync(0xffffffffu, b, 2);
            i0 = rcp(a); i1 = rcp(b);
        };

        {
            bar_sync(my_bar);
            wg_fence();
            mma_tile<0>(o, q, ring16, 0);
            mbar_wait(full + 8, 0);
            wg_fence();
            mma_tile<0>(s, q, ring16 + T16, 0);
            bar_arrive(other_bar);
            wg_wait<1>();
            TA(20);
            release_at<0>(rel);
            pin(o);
            l0 = 0.f; l1 = 0.f;
            exp_range(o, 0, 64, l0, l1);
            mbar_wait(full + 16, 1);
            wg_wait<0>();
            if (unsafe(true, l0, l1)) softmax_true_max(o, true, 0.f, 0.f, l0, l1);
        }
        uint32_t qsrc = my_stash;
        float il0 = 0.f, il1 = 0.f;
        auto step = [&](auto odd_c, int m) {
            constexpr int ODD = decltype(odd_c)::value;
            constexpr int KS = ODD ? 3 : 1, VS = ODD ? 0 : 2;
            [[maybe_unused]] const int it = 2 * m + ODD;
            const uint32_t ph = m & 1;
            TC(0);
            bar_sync(my_bar);
            TC(1);
            if (ODD || m) {
                wg_fence();
                mma_tile<0>(s, q, ring16 + KS * T16, 0);
            }
            TC(2);
            if (!ODD) {
                if ((m & 7) == 0 && m) {
#pragma unroll
                    for (int i = FSPLIT; i < 8; i++)
                        sts128(qsrc + i * 512,
                               pack_bf16(o[8 * i] * il0, o[8 * i + 1] * il0), pack_bf16(o[8 * i + 2] * il1, o[8 * i + 3] * il1),
                               pack_bf16(o[8 * i + 4] * il0, o[8 * i + 5] * il0), pack_bf16(o[8 * i + 6] * il1, o[8 * i + 7] * il1));
                    qsrc += m == 24 ? -2 * TILE_BYTES : TILE_BYTES;
                }
                wg_fence();
            }
#pragma unroll
            for (int ks = 0; ks < 8; ks++) {
                wgmma_rs<1>(o, p[4 * ks], p[4 * ks + 1], p[4 * ks + 2], p[4 * ks + 3], desc_nmajor(ring16 + VS * T16, ks),
                            (ks == 0 && !ODD) ? ((m & 7) != 0) : 1);
                if (ks == SPLIT / 8 - 1 || ks == 7) wg_commit();
            }
            TC(3);
            bar_arrive(other_bar);
            const bool last = ODD && (m & 7) == 7;
            if (last) {
                inv_sums(il0, il1);
                l0 = 0.f; l1 = 0.f; l_hi = L_HI;
            }
            wg_wait<1>();
            TA(21 + it);
            TC(4);
            release_at<8 * KS>(rel);
            const bool newq = (m & 7) == 7;
            if (!ODD) {
                lds128_if<0>(newq, qsrc, q[0], q[1], q[2], q[3]);
                lds128_if<512>(newq, qsrc, q[4], q[5], q[6], q[7]);
                lds128_if<1024>(newq, qsrc, q[8], q[9], q[10], q[11]);
            }
            pin(s);
            float u0 = l0, u1 = l1;
            exp_range(s, 0, SPLIT, u0, u1);
            mbar_wait_hot(full + 8 * (KS ^ 2), ph ^ 1);
            if (!ODD) {
                lds128_if<1536>(newq, qsrc, q[12], q[13], q[14], q[15]);
                lds128_if<2048>(newq, qsrc, q[16], q[17], q[18], q[19]);
            }
            TC(5);
            wg_wait<0>();
            release_at<8 * VS>(rel);
            pin(o);
            exp_range(s, SPLIT, 64, u0, u1);
            TC(6);
            mbar_wait_hot(full + 8 * (VS ^ 2), ODD ? ph : ph ^ 1);
            if (!ODD) {
                lds128_if<2560>(newq, qsrc, q[20], q[21], q[22], q[23]);
                lds128_if<3072>(newq, qsrc, q[24], q[25], q[26], q[27]);
                lds128_if<3584>(newq, qsrc, q[28], q[29], q[30], q[31]);
            } else if (last) {
#pragma unroll
                for (int i = 0; i < FSPLIT; i++)
                    sts128(qsrc + i * 512,
                           pack_bf16(o[8 * i] * il0, o[8 * i + 1] * il0), pack_bf16(o[8 * i + 2] * il1, o[8 * i + 3] * il1),
                           pack_bf16(o[8 * i + 4] * il0, o[8 * i + 5] * il0), pack_bf16(o[8 * i + 6] * il1, o[8 * i + 7] * il1));
            }
            if (unsafe(last, u0, u1)) softmax_true_max(s, last, l0, l1, u0, u1);
            l0 = u0; l1 = u1;
            TC(7);
            TF(3 + it);
        };
#pragma unroll 1
        for (int m = 0;; m++) {
            step(cint<0>(), m);
            if (m == 31) break;
            step(cint<1>(), m);
        }
        uint32_t ob[64];
        const uint32_t t128 = threadIdx.x & 127;
        uint32_t ep, tag;
        const uint32_t half = 0x8000u;
        auto send = [&](uint4* dst, const float* a) {
            asm volatile("st.relaxed.gpu.global.v4.u32 [%0], {%1, %2, %3, %4};" ::"l"(dst), "r"(lop3<0xD8>(pack_bf16(a[0], a[1]), tag, 0x10000u)),
                         "r"(pack_bf16(a[2], a[3])), "r"(pack_bf16(a[4], a[5])), "r"(pack_bf16(a[6], a[7])) : "memory");
        };
        auto hint = [&](int dst, int job) {
            asm volatile("st.relaxed.gpu.global.u32 [%0], %1;" ::"l"((uint32_t*)(sc->flag + (qt * 8 + dst) * 32 + job) + (warp & 3)), "r"(ep) : "memory");
        };
        float a32[32], own[32];
        auto half_mma = [&](const uint32_t* a, const uint32_t* b, uint32_t t16, int accumulate) {
            wg_fence();
#pragma unroll
            for (int ks = 0; ks < 8; ks++) wgmma_rs64(a32, a[4 * ks], a[4 * ks + 1], a[4 * ks + 2], a[4 * ks + 3], desc_nmajor(t16, ks), ks ? 1 : accumulate);
#pragma unroll
            for (int ks = 0; ks < 8; ks++) wgmma_rs64(a32, b[4 * ks], b[4 * ks + 1], b[4 * ks + 2], b[4 * ks + 3], desc_nmajor(t16, 8 + ks), 1);
            wg_commit();
        };
        auto block_mma = [&](uint32_t sb, uint32_t ph, bool pass_turn) {
            mbar_wait(full + 8 * sb, ph);
            bar_sync(my_bar);
            half_mma(q, ob, ring16 + sb * T16, zero);
            mbar_wait(full + 8 * sb + 8, ph);
            half_mma(ob + 32, p, ring16 + (sb + 1) * T16, 1);
            if (pass_turn) bar_arrive(other_bar);
        };
        auto send_strips = [&](int u) {
            const uint32_t t = opaque(t128);
            const int d0 = (grp & 4) ^ (4 * u);
            uint4* dst = sc->part + (((qt * 8 + d0) * 9 + u) * 2 + wg) * 512 + (grp & 3) * 128 + t;
#pragma unroll
            for (int i = 0; i < 4; i++) send(dst + i * 9 * 1024, a32 + 8 * i);
            if ((t & 31) < 4) hint(d0 + (t & 31), u * 8 + (grp & 3) * 2 + wg);
        };
        uint32_t xs[4], gs[4];
        {
            [[maybe_unused]] const int c = 9;
            TS(0);
            auto fetch_o = [&](int lo, int hi) {
#pragma unroll
                for (int i = lo; i < hi; i++)
                    lds128(qsrc + (1 + (i >> 3)) * TILE_BYTES + (i & 7) * 512, ob[4 * i], ob[4 * i + 1], ob[4 * i + 2], ob[4 * i + 3]);
            };
            fetch_o(0, 3);
            bar_sync(my_bar);
            wg_fence();
            mma_tile<1>(o, p, ring16 + 3 * T16, 1);
            sched_fence(zero);
            inv_sums(il0, il1);
            asm volatile("" : "+f"(il0), "+f"(il1));
            sched_fence(zero);
            fetch_o(3, 6);
            wg_fence();
#pragma unroll
            for (int ks = 0; ks < 8; ks++) {
                wgmma_rs64(a32, q[4 * ks], q[4 * ks + 1], q[4 * ks + 2], q[4 * ks + 3], desc_nmajor(ring16, ks), ks);
                if (ks == 3) { wg_commit(); sched_fence(zero); fetch_o(6, 8); wg_fence(); }
            }
            TS(1);
#pragma unroll
            for (int ks = 0; ks < 8; ks++) wgmma_rs64(a32, ob[4 * ks], ob[4 * ks + 1], ob[4 * ks + 2], ob[4 * ks + 3], desc_nmajor(ring16, 8 + ks), 1);
            wg_commit();
            TS(2);
            bar_arrive(other_bar);
            wg_wait<1>();
            release_at<24>(rel);
            pin(o);
#pragma unroll
            for (int i = 0; i < 32; i++) {
                const float r = (i & 1) ? il1 : il0;
                asm volatile("cvt.rn.bf16x2.f32 %0, %1, %2;" : "=r"(p[i]) : "f"(o[2 * i + 1] * r), "f"(o[2 * i] * r));
                if ((i & 7) == 7) fetch_o(8 + (i >> 3) * 2, 10 + (i >> 3) * 2);
            }
            TS(3);
            mbar_wait(full + 8, 0);
            wg_wait<0>();
            release_at<0>(rel);
            __syncwarp();
            if (lane == 0) mbar_arrive(vacant);
            TS(4);
            bar_sync(my_bar);
            half_mma(ob + 32, p, ring16 + T16, 1);
            TS(5);
            bar_arrive(other_bar);
            TR(66);
            TG(113);
            mbar_wait(routed, 0);
            asm volatile("ld.shared.u32 %0, [%1];" : "=r"(ep) : "r"(epoch));
            tag = ep << 16;
            const uint4* src = sc->gate + (blockIdx.x * 5 + 4) * 512 + threadIdx.x;
            asm volatile("ld.global.cg.v4.u32 {%0, %1, %2, %3}, [%4];" : "=r"(xs[0]), "=r"(xs[1]), "=r"(xs[2]), "=r"(xs[3]) : "l"(src));
            asm volatile("ld.global.cg.v4.u32 {%0, %1, %2, %3}, [%4];" : "=r"(gs[0]), "=r"(gs[1]), "=r"(gs[2]), "=r"(gs[3]) : "l"(src + 256));
            sched_fence(zero);
            wg_wait<0>();
            TS(6);
            release_at<8>(rel);
            pin(a32);
            send_strips(0);
            TS(7);
        }
        uint32_t v[4][4];
        auto stale = [&]() {
            return __any_sync(0xffffffffu, lop3<0xA8>(lop3<0x7E>(v[0][0], v[1][0], tag), lop3<0x7E>(v[2][0], v[3][0], tag), 0x10000u));
        };
        auto recv = [&](int u) {
            mbar_wait(rfull + 16 * u + 8 * wg, 0);
#pragma unroll
            for (int i = 0; i < 4; i++)
                lds128(stash + (u >= 6 ? u - 6 : u) * 16384 + wg * 8192 + i * 2048 + t128 * 16, v[i][0], v[i][1], v[i][2], v[i][3]);
            if (stale()) {
                const uint4* src = sc->part + (((qt * 8 + grp) * 9 + u) * 2 + wg) * 512 + opaque(t128);
                do {
#pragma unroll
                    for (int i = 0; i < 4; i++)
                        asm volatile("ld.relaxed.gpu.global.v4.u32 {%0, %1, %2, %3}, [%4];" : "=r"(v[i][0]), "=r"(v[i][1]), "=r"(v[i][2]), "=r"(v[i][3])
                                     : "l"(src + i * 128) : "memory");
                } while (stale());
            }
            if (u < 3 && lane == 0) mbar_arrive(rdone + (u * 2 + wg) * 8);
        };
        auto accumulate = [&](float* dst, int stride) {
#pragma unroll
            for (int i = 0; i < 4; i++) {
                float* a = dst + stride * i;
                a[0] += bf_lo(v[i][0]);
                a[1] += __uint_as_float(lop3<0xEC>(v[i][0], half, 0xfffe0000u));
#pragma unroll
                for (int k = 1; k < 4; k++) { a[2 * k] += bf_lo(v[i][k]); a[2 * k + 1] += bf_hi(v[i][k]); }
            }
        };
        auto gate = [](uint32_t x2, uint32_t g2, float lo, float hi) {
            uint32_t sv = pack_bf16(lo, hi);
            asm("mul.rn.bf16x2 %0, %0, %1;" : "+r"(sv) : "r"(g2));
            asm("add.rn.bf16x2 %0, %0, %1;" : "+r"(sv) : "r"(x2));
            return sv;
        };
        uint4* const outbox = sc->part + qt * (8 * 9 * 1024) + wg * 512 + t128;
        auto step_o = [&](int f) {
            [[maybe_unused]] const int c = f;
            const uint32_t sb = (f & 1) ? 0 : 2;
            block_mma(sb, (((f + 3) >> 1) ^ f) & 1, true);
            wg_wait<1>();
            const uint32_t rl = rel && f < 7 ? rel + 8 * sb : 0;
            release_at<0>(rl);
            if (f >= 1) recv(f - 1);
            wg_wait<0>();
            TS(0);
            release_at<8>(rl);
            pin(a32);
            if (f == 0) {
                send_strips(1);
            } else {
                const int d = (grp + f) & 7;
#pragma unroll
                for (int i = 0; i < 4; i++) send(outbox + (d * 9 + f + 1) * 1024 + i * 128, a32 + 8 * i);
                if (lane == 0) hint(d, 14 + 2 * f + wg);
            }
            TS(1);
        };
        {
            float st[8] = {};
#pragma unroll 1
            for (int f = 0; f < 3; f++) {
                [[maybe_unused]] const int c = f;
                step_o(f);
                if (f >= 1) accumulate(st, 0);
                TS(2);
            }
            uint32_t w[4];
#pragma unroll
            for (int i = 0; i < 4; i++) w[i] = gate(xs[i], gs[i], st[2 * i], st[2 * i + 1]);
            const bool odd = lane & 1;
            const uint32_t r0 = __shfl_xor_sync(0xffffffffu, odd ? w[0] : w[2], 1), r1 = __shfl_xor_sync(0xffffffffu, odd ? w[1] : w[3], 1);
            uint2* dst = (uint2*)out + (qt * 128 + warp * 16 + (lane >> 2)) * (DM / 4) + 128 + grp * 4 + (lane & 1) * 2 + ((lane >> 1) & 1);
            dst[0] = odd ? make_uint2(r0, w[2]) : make_uint2(w[0], r0);
            dst[2 * DM] = odd ? make_uint2(r1, w[3]) : make_uint2(w[1], r1);
        }
#pragma unroll
        for (int i = 0; i < 32; i++) own[i] = 0.f;
#pragma unroll 1
        for (int f = 3; f < 8; f++) {
            [[maybe_unused]] const int c = f;
            step_o(f);
            accumulate(own, 8);
            TS(2);
        }
        {
            [[maybe_unused]] const int c = 8;
            recv(7);
            accumulate(own, 8);
            TS(7);
            block_mma(2, 1, wg == 0);
            TR(71);
            TS(0);
            recv(8);
            accumulate(own, 8);
            TS(1);
            wg_wait<1>();
            uint32_t xv[16], gv[16];
            mbar_wait(xgfull, 0);
            if (lane == 0) mbar_arrive(alldone);
#pragma unroll
            for (int j = 0; j < 4; j++) {
                lds128(stash + 3 * 16384 + j * 8192 + threadIdx.x * 16, xv[4 * j], xv[4 * j + 1], xv[4 * j + 2], xv[4 * j + 3]);
                lds128(stash + 3 * 16384 + j * 8192 + 4096 + threadIdx.x * 16, gv[4 * j], gv[4 * j + 1], gv[4 * j + 2], gv[4 * j + 3]);
            }
            TS(2);
            wg_wait<0>();
            pin(a32);
#pragma unroll
            for (int i = 0; i < 32; i++) own[i] += a32[i];
            TS(3);
            const uint32_t tb = ring + warp * 2048;
#pragma unroll
            for (int j = 0; j < 4; j++)
                stsm4(tb + (lane & 15) * 128 + (((2 * j + (lane >> 4)) ^ (lane & 7)) << 4),
                      gate(xv[4 * j], gv[4 * j], own[8 * j], own[8 * j + 1]), gate(xv[4 * j + 1], gv[4 * j + 1], own[8 * j + 2], own[8 * j + 3]),
                      gate(xv[4 * j + 2], gv[4 * j + 2], own[8 * j + 4], own[8 * j + 5]), gate(xv[4 * j + 3], gv[4 * j + 3], own[8 * j + 6], own[8 * j + 7]));
            __syncwarp();
#pragma unroll
            for (int j = 0; j < 4; j++) {
                const uint32_t row = j * 4 + (lane >> 3);
                uint4 v;
                lds128(tb + row * 128 + (((lane & 7) ^ (row & 7)) << 4), v.x, v.y, v.z, v.w);
                ((uint4*)out)[(qt * 128 + warp * 16 + row) * (DM / 8) + grp * 8 + (lane & 7)] = v;
            }
        }
        TR(73);
        TG(111);
    }
}

typedef CUresult (*EncodeFn)(CUtensorMap*, CUtensorMapDataType, cuuint32_t, void*, const cuuint64_t*, const cuuint64_t*,
                             const cuuint32_t*, const cuuint32_t*, CUtensorMapInterleave, CUtensorMapSwizzle,
                             CUtensorMapL2promotion, CUtensorMapFloatOOBfill);

void make_map(EncodeFn enc, CUtensorMap* tm, const void* ptr, uint64_t cols, uint64_t rows) {
    cuuint64_t gd[2] = {cols, rows};
    cuuint64_t gs[1] = {cols * 2};
    cuuint32_t bd[2] = {64, 128};
    cuuint32_t es[2] = {1, 1};
    enc(tm, CU_TENSOR_MAP_DATA_TYPE_BFLOAT16, 2, const_cast<void*>(ptr), gd, gs, bd, es, CU_TENSOR_MAP_INTERLEAVE_NONE,
        CU_TENSOR_MAP_SWIZZLE_128B, CU_TENSOR_MAP_L2_PROMOTION_L2_256B, CU_TENSOR_MAP_FLOAT_OOB_FILL_NONE);
}

}

extern "C" void kernel_launch(void* const* d_in, const int* in_sizes, int n_in, void* d_out, int out_size) {
    const __nv_bfloat16* x = (const __nv_bfloat16*)d_in[0];
    const __nv_bfloat16* wr = (const __nv_bfloat16*)d_in[6];
    __nv_bfloat16* out = (__nv_bfloat16*)d_out;

    EncodeFn enc = nullptr;
    cudaDriverEntryPointQueryResult qr;
    cudaGetDriverEntryPoint("cuTensorMapEncodeTiled", (void**)&enc, cudaEnableDefault, &qr);
    CUtensorMap tm_x, tm_wq, tm_k, tm_v, tm_wo, tm_g, tm_u, tm_d;
    {
        cuuint64_t gd[3] = {64, SEQ, DM / 64};
        cuuint64_t gs[2] = {DM * 2, 128};
        cuuint32_t bd[3] = {64, 64, 2};
        cuuint32_t es[3] = {1, 1, 1};
        enc(&tm_x, CU_TENSOR_MAP_DATA_TYPE_BFLOAT16, 3, d_in[0], gd, gs, bd, es, CU_TENSOR_MAP_INTERLEAVE_NONE,
            CU_TENSOR_MAP_SWIZZLE_128B, CU_TENSOR_MAP_L2_PROMOTION_L2_256B, CU_TENSOR_MAP_FLOAT_OOB_FILL_NONE);
    }
    make_map(enc, &tm_k, d_in[1], DH, (uint64_t)NH * SEQ);
    make_map(enc, &tm_v, d_in[2], DH, (uint64_t)NH * SEQ);
    make_map(enc, &tm_wq, d_in[3], NH * DH, DM);
    make_map(enc, &tm_wo, d_in[4], DM, NH * DH);
    make_map(enc, &tm_g, d_in[7], FF, DM);
    make_map(enc, &tm_u, d_in[8], FF, DM);
    make_map(enc, &tm_d, d_in[9], DM, FF);
    cudaFuncSetAttribute(fused_attn_kernel, cudaFuncAttributeMaxDynamicSharedMemorySize, SMEM_BYTES);

    Scratch* sc = nullptr;
    cudaGetSymbolAddress((void**)&sc, g_scratch);

    cudaLaunchConfig_t cfg = {};
    cfg.gridDim = dim3(N_MAIN + N_MOE);
    cfg.blockDim = dim3(384);
    cfg.dynamicSmemBytes = SMEM_BYTES;
    cfg.stream = cudaStreamPerThread;
    cudaLaunchAttribute at[1];
    at[0].id = cudaLaunchAttributeClusterDimension;
    at[0].val.clusterDim.x = 2; at[0].val.clusterDim.y = 1; at[0].val.clusterDim.z = 1;
    cfg.attrs = at; cfg.numAttrs = 1;
    cudaLaunchKernelEx(&cfg, fused_attn_kernel, x, wr, out, sc, tm_x, tm_wq, tm_k, tm_v, tm_wo, tm_g, tm_u, tm_d);
}
```

```cpp
#include <cuda_runtime.h>
#include <cuda.h>
#include <cuda_bf16.h>
#include <stdint.h>

namespace {

constexpr int SEQ = 2048, DM = 640, NH = 32, DH = 128, FF = 1728, CAP = 8;
constexpr int NSLOT = 4;
constexpr int TILE_BYTES = 32768;
constexpr uint32_t RING_OFFSET = 1024;
constexpr int SMEM_BYTES = (NSLOT + 3) * TILE_BYTES + 416 + 1408 + 96;
constexpr int N_MAIN = 128, N_MOE = 4;

struct Scratch {
    uint4 part[16 * 8 * 9 * 2 * 4 * 128];
    uint4 gate[N_MAIN * 5 * 2 * 256];
    uint4 flag[16 * 8 * 32];
    uint4 qoff[16 * 4 * 2048];
    uint32_t flag_q[16];
    uint4 rare[N_MAIN * 17 * 256];
    float y[N_MOE * CAP * DM];
    uint2 routed[CAP * DM / 4];
    uint2 stat[SEQ];
    float r[SEQ];
    int idx[CAP];
    uint32_t flag_r[N_MOE], flag_y[N_MOE], flag_u[N_MOE];
    uint32_t epoch[N_MAIN + N_MOE];
};
__device__ Scratch g_scratch;

__device__ __forceinline__ uint32_t smem_u32(const void* p) { return (uint32_t)__cvta_generic_to_shared(p); }
__device__ __forceinline__ void mbar_init(uint32_t bar, uint32_t cnt) {
    asm volatile("mbarrier.init.shared::cta.b64 [%0], %1;" ::"r"(bar), "r"(cnt) : "memory");
}
#define HOTW 2
__device__ __forceinline__ void mbar_wait(uint32_t bar, uint32_t parity) {
    asm volatile(
        "{\n.reg .pred p;\n"
        "LOOP:\n"
        "mbarrier.try_wait.parity.shared::cta.b64 p, [%0], %1;\n"
        "@!p bra.uni LOOP;\n"
        "DONE:\n}\n" ::"r"(bar), "r"(parity) : "memory");
}
__device__ __forceinline__ void mbar_wait_hot(uint32_t bar, uint32_t parity) {
    asm volatile(
        "{\n.reg .pred p;\n.reg .u32 c;\n"
        "mbarrier.test_wait.parity.shared::cta.b64 p, [%0], %1;\n"
        "@p bra.uni DONE;\n"
        "mov.u32 c, 0;\n"
        "LOOP:\n"
        "mbarrier.try_wait.parity.shared::cta.b64 p, [%0], %1;\n"
        "@p bra.uni DONE;\n"
        "add.u32 c, c, 1;\n"
        "setp.lt.u32 p, c, 2000000;\n"
        "@p bra.uni LOOP;\n"
        "trap;\n"
        "DONE:\n}\n" ::"r"(bar), "r"(parity) : "memory");
}
__device__ __forceinline__ void mbar_wait_bounded(uint32_t bar, uint32_t parity) {
    asm volatile(
        "{\n.reg .pred p;\n.reg .u32 c;\n"
        "mov.u32 c, 0;\n"
        "LOOP:\n"
        "mbarrier.try_wait.parity.shared::cta.b64 p, [%0], %1;\n"
        "@p bra.uni DONE;\n"
        "add.u32 c, c, 1;\n"
        "setp.lt.u32 p, c, 2000000;\n"
        "@p bra.uni LOOP;\n"
        "trap;\n"
        "DONE:\n}\n" ::"r"(bar), "r"(parity) : "memory");
}
__device__ __forceinline__ void mbar_wait_sleep(uint32_t bar, uint32_t parity) {
    asm volatile(
        "{\n.reg .pred p;\n.reg .u32 c;\n"
        "mov.u32 c, 0;\n"
        "LOOP:\n"
        "mbarrier.test_wait.parity.shared::cta.b64 p, [%0], %1;\n"
        "@p bra.uni DONE;\n"
        "nanosleep.u32 500;\n"
        "add.u32 c, c, 1;\n"
        "setp.lt.u32 p, c, 1000000;\n"
        "@p bra.uni LOOP;\n"
        "trap;\n"
        "DONE:\n}\n" ::"r"(bar), "r"(parity) : "memory");
}
__device__ __forceinline__ void mbar_expect_tx(uint32_t bar, uint32_t bytes) {
    asm volatile("mbarrier.arrive.expect_tx.shared::cta.b64 _, [%0], %1;" ::"r"(bar), "r"(bytes) : "memory");
}
template <int OFF>
__device__ __forceinline__ void release_at(uint32_t bar) {
    asm volatile(
        "{\n.reg .pred p;\n"
        "setp.ne.u32 p, %0, 0;\n"
        "@p mbarrier.arrive.shared::cluster.b64 _, [%0 + %1];\n}\n" ::"r"(bar), "n"(OFF) : "memory");
}
__device__ __forceinline__ void sched_fence(int zero) {
    asm volatile("{\n.reg .pred p;\n.reg .u32 c;\nsetp.ne.s32 p, %0, 0;\n@p mov.u32 c, %%clock;\n@p st.shared.u32 [%0], c;\n}\n" ::"r"(zero) : "memory");
}
__device__ __forceinline__ bool elect_one() {
    uint32_t r;
    asm volatile("{\n.reg .pred p;\nelect.sync _|p, 0xffffffff;\nselp.u32 %0, 1, 0, p;\n}\n" : "=r"(r));
    return r;
}
__device__ __forceinline__ uint32_t opaque(uint32_t v) {
    uint32_t r;
    asm volatile("mov.u32 %0, %1;" : "=r"(r) : "r"(v));
    return r;
}
__device__ __forceinline__ void tma_2d(uint32_t dst, const CUtensorMap* tm, uint32_t bar, int c0, int c1) {
    asm volatile(
        "cp.async.bulk.tensor.2d.shared::cluster.global.mbarrier::complete_tx::bytes [%0], [%1, {%3, %4}], [%2];"
        ::"r"(dst), "l"(tm), "r"(bar), "r"(c0), "r"(c1) : "memory");
}
__device__ __forceinline__ void tma_3d(uint32_t dst, const CUtensorMap* tm, uint32_t bar, int c0, int c1, int c2) {
    asm volatile(
        "cp.async.bulk.tensor.3d.shared::cluster.global.mbarrier::complete_tx::bytes [%0], [%1, {%3, %4, %5}], [%2];"
        ::"r"(dst), "l"(tm), "r"(bar), "r"(c0), "r"(c1), "r"(c2) : "memory");
}
__device__ __forceinline__ void tma_2d_mc(uint32_t dst, const CUtensorMap* tm, uint32_t bar, int c0, int c1) {
    asm volatile(
        "cp.async.bulk.tensor.2d.shared::cluster.global.mbarrier::complete_tx::bytes.multicast::cluster "
        "[%0], [%1, {%3, %4}], [%2], %5;"
        ::"r"(dst), "l"(tm), "r"(bar), "r"(c0), "r"(c1), "h"((uint16_t)3) : "memory");
}
__device__ __forceinline__ void tma_prefetch(const CUtensorMap* tm, int c0, int c1) {
    asm volatile("cp.async.bulk.prefetch.tensor.2d.L2.global [%0, {%1, %2}];" ::"l"(tm), "r"(c0), "r"(c1) : "memory");
}
__device__ __forceinline__ void mbar_arrive(uint32_t bar) {
    asm volatile("mbarrier.arrive.shared::cta.b64 _, [%0];" ::"r"(bar) : "memory");
}
__device__ __forceinline__ void flag_set(uint32_t* f, uint32_t v) {
    asm volatile("st.release.gpu.global.u32 [%0], %1;" ::"l"(f), "r"(v) : "memory");
}
template <int SLEEP_NS = 0>
__device__ __forceinline__ void flag_wait(const uint32_t* f, uint32_t v) {
    asm volatile(
        "{\n.reg .pred p;\n.reg .u32 c;\n"
        "LOOP:\n"
        "setp.ne.u32 p, %2, 0;\n"
        "@p nanosleep.u32 %2;\n"
        "ld.acquire.gpu.global.u32 c, [%0];\n"
        "setp.ne.u32 p, c, %1;\n"
        "@p bra LOOP;\n}\n" ::"l"(f), "r"(v), "n"(SLEEP_NS) : "memory");
}
template <int SLEEP_NS>
__device__ __forceinline__ void flag_wait_bounded(const uint32_t* f, uint32_t v) {
    asm volatile(
        "{\n.reg .pred p;\n.reg .u32 c, n;\n"
        "mov.u32 n, 0;\n"
        "LOOP:\n"
        "setp.ne.u32 p, %2, 0;\n"
        "@p nanosleep.u32 %2;\n"
        "ld.acquire.gpu.global.u32 c, [%0];\n"
        "setp.eq.u32 p, c, %1;\n"
        "@p bra DONE;\n"
        "add.u32 n, n, 1;\n"
        "setp.lt.u32 p, n, %3;\n"
        "@p bra LOOP;\n"
        "trap;\n"
        "DONE:\n}\n" ::"l"(f), "r"(v), "n"(SLEEP_NS), "n"(2000000) : "memory");
}
__device__ __forceinline__ void hmma(float (&d)[4], uint32_t a0, uint32_t a1, uint32_t a2, uint32_t a3, uint32_t b0, uint32_t b1) {
    asm volatile("mma.sync.aligned.m16n8k16.row.col.f32.bf16.bf16.f32 {%0,%1,%2,%3}, {%4,%5,%6,%7}, {%8,%9}, {%0,%1,%2,%3};"
                 : "+f"(d[0]), "+f"(d[1]), "+f"(d[2]), "+f"(d[3]) : "r"(a0), "r"(a1), "r"(a2), "r"(a3), "r"(b0), "r"(b1));
}
__device__ __forceinline__ void hmma8(float (&d)[4], uint32_t a0, uint32_t a1, uint32_t b0) {
    asm volatile("mma.sync.aligned.m16n8k8.row.col.f32.bf16.bf16.f32 {%0,%1,%2,%3}, {%4,%5}, {%6}, {%0,%1,%2,%3};"
                 : "+f"(d[0]), "+f"(d[1]), "+f"(d[2]), "+f"(d[3]) : "r"(a0), "r"(a1), "r"(b0));
}
__device__ __forceinline__ void ldsm4(uint32_t addr, uint32_t& a, uint32_t& b, uint32_t& c, uint32_t& d) {
    asm volatile("ldmatrix.sync.aligned.m8n8.x4.shared.b16 {%0, %1, %2, %3}, [%4];"
                 : "=r"(a), "=r"(b), "=r"(c), "=r"(d) : "r"(addr) : "memory");
}
__device__ __forceinline__ void stsm4(uint32_t addr, uint32_t a, uint32_t b, uint32_t c, uint32_t d) {
    asm volatile("stmatrix.sync.aligned.m8n8.x4.shared.b16 [%4], {%0, %1, %2, %3};"
                 ::"r"(a), "r"(b), "r"(c), "r"(d), "r"(addr) : "memory");
}
__device__ __forceinline__ uint32_t bf2_sub(uint32_t a, uint32_t b) {
    uint32_t d;
    asm("sub.rn.bf16x2 %0, %1, %2;" : "=r"(d) : "r"(a), "r"(b));
    return d;
}
template <int LUT>
__device__ __forceinline__ uint32_t lop3(uint32_t a, uint32_t b, uint32_t c) {
    uint32_t d;
    asm("lop3.b32 %0, %1, %2, %3, %4;" : "=r"(d) : "r"(a), "r"(b), "r"(c), "n"(LUT));
    return d;
}
__device__ __forceinline__ float rcp(float x) {
    float y;
    asm("rcp.approx.ftz.f32 %0, %1;" : "=f"(y) : "f"(x));
    return y;
}
__device__ __forceinline__ void bar_sync(int id) { asm volatile("bar.sync %0, 256;" ::"r"(id) : "memory"); }
__device__ __forceinline__ void bar_arrive(int id) { asm volatile("bar.arrive %0, 256;" ::"r"(id) : "memory"); }
__device__ __forceinline__ void wg_fence() { asm volatile("wgmma.fence.sync.aligned;" ::: "memory"); }
__device__ __forceinline__ void wg_commit() { asm volatile("wgmma.commit_group.sync.aligned;" ::: "memory"); }
template <int N> __device__ __forceinline__ void wg_wait() { asm volatile("wgmma.wait_group.sync.aligned %0;" ::"n"(N) : "memory"); }
template <int N>
__device__ __forceinline__ void pin(float (&d)[N]) {
#pragma unroll
    for (int i = 0; i < N; i++) asm volatile("" : "+f"(d[i])::"memory");
}
__device__ __forceinline__ uint32_t pack_bf16(float lo, float hi) {
    uint32_t r;
    asm("cvt.rn.bf16x2.f32 %0, %1, %2;" : "=r"(r) : "f"(hi), "f"(lo));
    return r;
}
__device__ __forceinline__ float bf_lo(uint32_t v) { return __uint_as_float(v << 16); }
__device__ __forceinline__ float bf_hi(uint32_t v) { return __uint_as_float(v & 0xffff0000u); }
__device__ __forceinline__ float bf_round(float v) { return __bfloat162float(__float2bfloat16_rn(v)); }
__device__ __forceinline__ float ex2(float x) {
    float y;
    asm("ex2.approx.ftz.f32 %0, %1;" : "=f"(y) : "f"(x));
    return y;
}
__device__ __forceinline__ void sts128(uint32_t addr, uint32_t a, uint32_t b, uint32_t c, uint32_t d) {
    asm volatile("st.shared.v4.b32 [%0], {%1, %2, %3, %4};" ::"r"(addr), "r"(a), "r"(b), "r"(c), "r"(d) : "memory");
}
__device__ __forceinline__ void lds128(uint32_t addr, uint32_t& a, uint32_t& b, uint32_t& c, uint32_t& d) {
    asm volatile("ld.shared.v4.b32 {%0, %1, %2, %3}, [%4];" : "=r"(a), "=r"(b), "=r"(c), "=r"(d) : "r"(addr) : "memory");
}

template <int OFF>
__device__ __forceinline__ void lds128_if(bool on, uint32_t addr, uint32_t& a, uint32_t& b, uint32_t& c, uint32_t& d) {
    asm volatile("{\n.reg .pred p;\nsetp.ne.u32 p, %5, 0;\n@p ld.shared.v4.b32 {%0, %1, %2, %3}, [%4 + %6];\n}\n"
                 : "+r"(a), "+r"(b), "+r"(c), "+r"(d) : "r"(addr), "r"((uint32_t)on), "n"(OFF) : "memory");
}

template <int TB>
__device__ __forceinline__ void wgmma_rs(float (&d)[64], uint32_t a0, uint32_t a1, uint32_t a2, uint32_t a3,
                                         uint64_t desc, int scale_d) {
    asm volatile(
        "{\n.reg .pred p;\nsetp.ne.b32 p, %69, 0;\n"
        "wgmma.mma_async.sync.aligned.m64n128k16.f32.bf16.bf16 "
        "{%0,%1,%2,%3,%4,%5,%6,%7,%8,%9,%10,%11,%12,%13,%14,%15,%16,%17,%18,%19,%20,%21,%22,%23,%24,%25,%26,%27,%28,%29,%30,%31,"
        "%32,%33,%34,%35,%36,%37,%38,%39,%40,%41,%42,%43,%44,%45,%46,%47,%48,%49,%50,%51,%52,%53,%54,%55,%56,%57,%58,%59,%60,%61,%62,%63},"
        "{%64,%65,%66,%67}, %68, p, 1, 1, %70;\n}\n"
        : "+f"(d[0]), "+f"(d[1]), "+f"(d[2]), "+f"(d[3]), "+f"(d[4]), "+f"(d[5]), "+f"(d[6]), "+f"(d[7]),
          "+f"(d[8]), "+f"(d[9]), "+f"(d[10]), "+f"(d[11]), "+f"(d[12]), "+f"(d[13]), "+f"(d[14]), "+f"(d[15]),
          "+f"(d[16]), "+f"(d[17]), "+f"(d[18]), "+f"(d[19]), "+f"(d[20]), "+f"(d[21]), "+f"(d[22]), "+f"(d[23]),
          "+f"(d[24]), "+f"(d[25]), "+f"(d[26]), "+f"(d[27]), "+f"(d[28]), "+f"(d[29]), "+f"(d[30]), "+f"(d[31]),
          "+f"(d[32]), "+f"(d[33]), "+f"(d[34]), "+f"(d[35]), "+f"(d[36]), "+f"(d[37]), "+f"(d[38]), "+f"(d[39]),
          "+f"(d[40]), "+f"(d[41]), "+f"(d[42]), "+f"(d[43]), "+f"(d[44]), "+f"(d[45]), "+f"(d[46]), "+f"(d[47]),
          "+f"(d[48]), "+f"(d[49]), "+f"(d[50]), "+f"(d[51]), "+f"(d[52]), "+f"(d[53]), "+f"(d[54]), "+f"(d[55]),
          "+f"(d[56]), "+f"(d[57]), "+f"(d[58]), "+f"(d[59]), "+f"(d[60]), "+f"(d[61]), "+f"(d[62]), "+f"(d[63])
        : "r"(a0), "r"(a1), "r"(a2), "r"(a3), "l"(desc), "r"(scale_d), "n"(TB));
}
__device__ __forceinline__ void wgmma_ss(float (&d)[64], uint64_t desc_a, uint64_t desc_b, int scale_d) {
    asm volatile(
        "{\n.reg .pred p;\nsetp.ne.b32 p, %66, 0;\n"
        "wgmma.mma_async.sync.aligned.m64n128k16.f32.bf16.bf16 "
        "{%0,%1,%2,%3,%4,%5,%6,%7,%8,%9,%10,%11,%12,%13,%14,%15,%16,%17,%18,%19,%20,%21,%22,%23,%24,%25,%26,%27,%28,%29,%30,%31,"
        "%32,%33,%34,%35,%36,%37,%38,%39,%40,%41,%42,%43,%44,%45,%46,%47,%48,%49,%50,%51,%52,%53,%54,%55,%56,%57,%58,%59,%60,%61,%62,%63},"
        "%64, %65, p, 1, 1, 0, 1;\n}\n"
        : "+f"(d[0]), "+f"(d[1]), "+f"(d[2]), "+f"(d[3]), "+f"(d[4]), "+f"(d[5]), "+f"(d[6]), "+f"(d[7]),
          "+f"(d[8]), "+f"(d[9]), "+f"(d[10]), "+f"(d[11]), "+f"(d[12]), "+f"(d[13]), "+f"(d[14]), "+f"(d[15]),
          "+f"(d[16]), "+f"(d[17]), "+f"(d[18]), "+f"(d[19]), "+f"(d[20]), "+f"(d[21]), "+f"(d[22]), "+f"(d[23]),
          "+f"(d[24]), "+f"(d[25]), "+f"(d[26]), "+f"(d[27]), "+f"(d[28]), "+f"(d[29]), "+f"(d[30]), "+f"(d[31]),
          "+f"(d[32]), "+f"(d[33]), "+f"(d[34]), "+f"(d[35]), "+f"(d[36]), "+f"(d[37]), "+f"(d[38]), "+f"(d[39]),
          "+f"(d[40]), "+f"(d[41]), "+f"(d[42]), "+f"(d[43]), "+f"(d[44]), "+f"(d[45]), "+f"(d[46]), "+f"(d[47]),
          "+f"(d[48]), "+f"(d[49]), "+f"(d[50]), "+f"(d[51]), "+f"(d[52]), "+f"(d[53]), "+f"(d[54]), "+f"(d[55]),
          "+f"(d[56]), "+f"(d[57]), "+f"(d[58]), "+f"(d[59]), "+f"(d[60]), "+f"(d[61]), "+f"(d[62]), "+f"(d[63])
        : "l"(desc_a), "l"(desc_b), "r"(scale_d));
}
__device__ __forceinline__ void wgmma_rs64(float (&d)[32], uint32_t a0, uint32_t a1, uint32_t a2, uint32_t a3,
                                           uint64_t desc, int scale_d) {
    asm volatile(
        "{\n.reg .pred p;\nsetp.ne.b32 p, %37, 0;\n"
        "wgmma.mma_async.sync.aligned.m64n64k16.f32.bf16.bf16 "
        "{%0,%1,%2,%3,%4,%5,%6,%7,%8,%9,%10,%11,%12,%13,%14,%15,%16,%17,%18,%19,%20,%21,%22,%23,%24,%25,%26,%27,%28,%29,%30,%31},"
        "{%32,%33,%34,%35}, %36, p, 1, 1, 1;\n}\n"
        : "+f"(d[0]), "+f"(d[1]), "+f"(d[2]), "+f"(d[3]), "+f"(d[4]), "+f"(d[5]), "+f"(d[6]), "+f"(d[7]),
          "+f"(d[8]), "+f"(d[9]), "+f"(d[10]), "+f"(d[11]), "+f"(d[12]), "+f"(d[13]), "+f"(d[14]), "+f"(d[15]),
          "+f"(d[16]), "+f"(d[17]), "+f"(d[18]), "+f"(d[19]), "+f"(d[20]), "+f"(d[21]), "+f"(d[22]), "+f"(d[23]),
          "+f"(d[24]), "+f"(d[25]), "+f"(d[26]), "+f"(d[27]), "+f"(d[28]), "+f"(d[29]), "+f"(d[30]), "+f"(d[31])
        : "r"(a0), "r"(a1), "r"(a2), "r"(a3), "l"(desc), "r"(scale_d));
}
__device__ __forceinline__ void wgmma_ss64(float (&d)[32], uint64_t desc_a, uint64_t desc_b, int scale_d) {
    asm volatile(
        "{\n.reg .pred p;\nsetp.ne.b32 p, %34, 0;\n"
        "wgmma.mma_async.sync.aligned.m64n64k16.f32.bf16.bf16 "
        "{%0,%1,%2,%3,%4,%5,%6,%7,%8,%9,%10,%11,%12,%13,%14,%15,%16,%17,%18,%19,%20,%21,%22,%23,%24,%25,%26,%27,%28,%29,%30,%31},"
        "%32, %33, p, 1, 1, 0, 1;\n}\n"
        : "+f"(d[0]), "+f"(d[1]), "+f"(d[2]), "+f"(d[3]), "+f"(d[4]), "+f"(d[5]), "+f"(d[6]), "+f"(d[7]),
          "+f"(d[8]), "+f"(d[9]), "+f"(d[10]), "+f"(d[11]), "+f"(d[12]), "+f"(d[13]), "+f"(d[14]), "+f"(d[15]),
          "+f"(d[16]), "+f"(d[17]), "+f"(d[18]), "+f"(d[19]), "+f"(d[20]), "+f"(d[21]), "+f"(d[22]), "+f"(d[23]),
          "+f"(d[24]), "+f"(d[25]), "+f"(d[26]), "+f"(d[27]), "+f"(d[28]), "+f"(d[29]), "+f"(d[30]), "+f"(d[31])
        : "l"(desc_a), "l"(desc_b), "r"(scale_d));
}
__device__ __forceinline__ uint64_t desc_kmajor(uint32_t tile16, int ks) {
    uint32_t lo = tile16 + ((ks >> 2) * 1024 + (ks & 3) * 2 + (1u << 16));
    return ((uint64_t)0x40000040u << 32) | lo;
}
__device__ __forceinline__ uint64_t desc_nmajor(uint32_t tile16, int ks) {
    uint32_t lo = tile16 + (ks * 128 + (1024u << 16));
    return ((uint64_t)0x40000040u << 32) | lo;
}
template <int TB>
__device__ __forceinline__ void mma_tile(float (&d)[64], const uint32_t* a, uint32_t tile16, int accumulate) {
#pragma unroll
    for (int ks = 0; ks < 8; ks++)
        wgmma_rs<TB>(d, a[4 * ks], a[4 * ks + 1], a[4 * ks + 2], a[4 * ks + 3],
                     TB ? desc_nmajor(tile16, ks) : desc_kmajor(tile16, ks), ks == 0 ? accumulate : 1);
    wg_commit();
}

template <int V> struct cint { static constexpr int value = V; };
#define GPF 126
#define XN 2
#define FINK 3
#define G4 0
#define EARLYA 0
#define PUTF 1
#define QB 1
#define QAT 110
#define FSPLIT 2
#define SPLIT 32

#define TRM(i)
#define TR(i)
#define TG(i)
#define PT(k)
#define TS(k)
#define TA(k)
#define TL(k)
#define TF(i)
#define TH(w, i)
#define TC(k)

__device__ __forceinline__ float silu_f(float v) { return v * rcp(1.f + ex2(v * -1.4426950408889634f)); }

__device__ __forceinline__ float inv_den(float var) {
    float r;
    asm("sqrt.approx.f32 %0, %1;" : "=f"(r) : "f"(bf_round(bf_round(var) + 1e-5f)));
    return rcp(bf_round(r));
}
__device__ __forceinline__ uint32_t normalise(uint32_t x2, uint32_t mm, float id) {
    const uint32_t d = bf2_sub(x2, mm);
    return pack_bf16(bf_lo(d) * id, bf_hi(d) * id);
}

__device__ __forceinline__ uint32_t silu2(uint32_t u) { return pack_bf16(silu_f(bf_lo(u)), silu_f(bf_hi(u))); }

__device__ __forceinline__ uint32_t silu2_ln(uint32_t u) {
    const float a = bf_lo(u), b = bf_hi(u);
    const float da = 1.f + ex2(a * -1.4426950408889634f), db = 1.f + ex2(b * -1.4426950408889634f);
    const float r = rcp(da * db);
    return pack_bf16(a * db * r, b * da * r);
}

__device__ __forceinline__ uint2 load_stat(Scratch* sc, int row) {
    uint2 v;
    asm volatile("ld.relaxed.gpu.global.v2.u32 {%0, %1}, [%2];" : "=r"(v.x), "=r"(v.y) : "l"(sc->stat + row) : "memory");
    return make_uint2(__byte_perm(v.x, 0, 0x1010), v.y);
}

constexpr int FSLOT = 6;
__device__ __forceinline__ void ffn_role(Scratch* sc, uint32_t ring, uint32_t ffull, uint32_t fempty, uint32_t alldone, int e, uint32_t ep, int warp,
                                         const __nv_bfloat16* __restrict__ x) {
    const uint32_t xs = ring + FSLOT * TILE_BYTES, hs = xs + 10 * 1024, cand = hs + 8 * 1024, sig = cand + 256;
    int tid;
    asm volatile("mov.u32 %0, %%tid.x;" : "=r"(tid));
    const int lane = tid & 31;
    [[maybe_unused]] const int wg = warp >> 2;
    const int nb = e == N_MOE - 1 ? 6 : 7, nkt = (nb + 1) >> 1;
    auto sync = [] { asm volatile("bar.sync 3, 256;" ::: "memory"); };
    if (tid < N_MOE) flag_wait(sc->flag_r + tid, ep);
    sync();
    TR(6);

    {
        uint32_t key[8];
#pragma unroll
        for (int i = 0; i < 8; i++) {
            const int j = warp * 256 + i * 32 + lane;
            const uint32_t u = __float_as_uint(__ldcg(sc->r + j) + 0.f);
            key[i] = (((u & 0x80000000u) ? ~u : (u | 0x80000000u)) & 0xffff0000u) | (uint32_t)(SEQ - j);
        }
#pragma unroll 1
        for (int k = 0; k < CAP; k++) {
            uint32_t b = key[0];
#pragma unroll
            for (int i = 1; i < 8; i++) b = max(b, key[i]);
            b = __reduce_max_sync(0xffffffffu, b);
#pragma unroll
            for (int i = 0; i < 8; i++) if (key[i] == b) key[i] = 0;
            if (lane == 0) asm volatile("st.shared.u32 [%0], %1;" ::"r"(cand + (warp * 8 + k) * 4), "r"(b) : "memory");
        }
    }
    sync();
    {
        uint32_t k0, k1, b = 0;
        asm volatile("ld.shared.v2.u32 {%0, %1}, [%2];" : "=r"(k0), "=r"(k1) : "r"(cand + lane * 8));
#pragma unroll 1
        for (int k = 0; k <= warp; k++) {
            b = __reduce_max_sync(0xffffffffu, max(k0, k1));
            if (k0 == b) k0 = 0;
            if (k1 == b) k1 = 0;
        }
        const int row = SEQ - (int)(b & 0xffffu);
        const uint2 st = load_stat(sc, row);
        uint4 v[3];
#pragma unroll
        for (int k = 0; k < 3; k++) v[k] = __ldg((const uint4*)(x + (size_t)row * DM) + min(lane + 32 * k, DM / 8 - 1));
#pragma unroll
        for (int k = 0; k < 3; k++) {
            const int i = lane + 32 * k;
            const float id = __uint_as_float(st.y);
            if (i < DM / 8)
                sts128(xs + (i >> 3) * 1024 + warp * 128 + (((i & 7) ^ warp) << 4), normalise(v[k].x, st.x, id), normalise(v[k].y, st.x, id),
                       normalise(v[k].z, st.x, id), normalise(v[k].w, st.x, id));
        }
        asm volatile("fence.proxy.async.shared::cta;" ::: "memory");
        if (lane == 0) {
            const float sg = bf_round(rcp(1.f + __expf(-__ldcg(sc->r + row))));
            asm volatile("st.shared.v2.b32 [%0], {%1, %2};" ::"r"(sig + warp * 8), "f"(sg), "r"(row) : "memory");
        }
    }
    sync();
    TR(7);

    {
        float acc[64];
        const int g = lane >> 2, t4 = lane & 3;
        auto block = [&](uint32_t a, uint32_t n, int step, int halves) {
#pragma unroll 1
            for (int i = 0; i < halves; i += 2, n += step) {
                const uint32_t s = n % FSLOT;
                mbar_wait(ffull + 8 * s, (n / FSLOT) & 1);
                const uint32_t a16 = (((a + i * 1024) & 0x3FFFFu) >> 4) | (1u << 16);
                const uint32_t b16 = ((ring + s * TILE_BYTES) & 0x3FFFFu) >> 4;
                auto mmas = [&](auto n_c) {
                    wg_fence();
#pragma unroll
                    for (int ks = 0; ks < decltype(n_c)::value; ks++)
                        wgmma_ss(acc, ((uint64_t)0x40000000u << 32) | (a16 + (ks >> 2) * 64 + (ks & 3) * 2), desc_nmajor(b16, ks), ks || i);
                    wg_commit();
                    wg_wait<0>();
                };
                if (i + 1 < halves) mmas(cint<8>());
                else mmas(cint<4>());
                if (lane == 0) mbar_arrive(fempty + 8 * s);
            }
            pin(acc);
        };
#pragma unroll 1
        for (int o = warp >> 2; o < nb; o += 2) {
            const bool pair = (o | 1) < nb;
            block(xs, 5 * (o & ~1) + (pair ? o & 1 : 0), pair ? 2 : 1, 10);
#pragma unroll
            for (int j = 0; j < 8; j++) {
                uint32_t h = pack_bf16(silu_f(bf_round(acc[4 * j])), silu_f(bf_round(acc[4 * j + 1])));
                asm("mul.rn.bf16x2 %0, %0, %1;" : "+r"(h) : "r"(pack_bf16(acc[32 + 4 * j], acc[33 + 4 * j])));
                asm volatile("st.shared.u32 [%0], %1;" ::"r"(hs + o * 1024 + g * 128 + ((j ^ g) << 4) + t4 * 4), "r"(h) : "memory");
            }
        }
        asm volatile("fence.proxy.async.shared::cta;" ::: "memory");
        sync();
        TR(8);
#pragma unroll 1
        for (int o = warp >> 2; o < 5; o += 2) {
            block(hs, 5 * nb + (o & ~1) * nkt + (o & 1), o < 4 ? 2 : 1, nb);
            if ((warp & 3) == 0) {
#pragma unroll
                for (int j = 0; j < 16; j++)
                    *(float2*)(sc->y + (e * CAP + g) * DM + o * 128 + j * 8 + t4 * 2) = make_float2(acc[4 * j], acc[4 * j + 1]);
            }
        }
    }
    sync();
    TR(9);
    if (tid == 0) flag_set(sc->flag_y + e, ep);
    if (tid < N_MOE) flag_wait(sc->flag_y + tid, ep);
    sync();
    if (lane == 0) mbar_arrive(alldone);
#pragma unroll 1
    for (int t = tid; t < 320; t += 256) {
        const int i = 2 * e * DM + t * 4;
        float4 y = __ldcg((const float4*)(sc->y + i));
#pragma unroll
        for (int j = 1; j < N_MOE; j++) {
            const float4 z = __ldcg((const float4*)(sc->y + j * CAP * DM + i));
            y.x += z.x; y.y += z.y; y.z += z.z; y.w += z.w;
        }
        float sg;
        int row;
        asm volatile("ld.shared.v2.b32 {%0, %1}, [%2];" : "=f"(sg), "=r"(row) : "r"(sig + (i / DM) * 8));
        const int o4 = (row * DM + i % DM) / 4;
        const uint2 v = __ldg((const uint2*)x + o4), st = load_stat(sc, row);
        uint32_t u0 = normalise(v.x, st.x, __uint_as_float(st.y)), u1 = normalise(v.y, st.x, __uint_as_float(st.y));
        asm("add.rn.bf16x2 %0, %0, %1;" : "+r"(u0) : "r"(pack_bf16(bf_round(y.x) * sg, bf_round(y.y) * sg)));
        asm("add.rn.bf16x2 %0, %0, %1;" : "+r"(u1) : "r"(pack_bf16(bf_round(y.z) * sg, bf_round(y.w) * sg)));
        sc->routed[i / 4] = make_uint2(silu2(u0), silu2(u1));
        if (i % DM == 0) sc->idx[i / DM] = row;
    }
    sync();
    TR(10);
    if (tid == 0) flag_set(sc->flag_u + e, ep);
}

__global__ void __launch_bounds__(384, 1)
fused_attn_kernel(const __nv_bfloat16* __restrict__ x, const __nv_bfloat16* __restrict__ wr,
                  __nv_bfloat16* __restrict__ out, Scratch* sc,
                  const __grid_constant__ CUtensorMap tm_x, const __grid_constant__ CUtensorMap tm_wq,
                  const __grid_constant__ CUtensorMap tm_k, const __grid_constant__ CUtensorMap tm_v,
                  const __grid_constant__ CUtensorMap tm_wo, const __grid_constant__ CUtensorMap tm_g,
                  const __grid_constant__ CUtensorMap tm_u, const __grid_constant__ CUtensorMap tm_d) {
    PT(0);
    extern __shared__ __align__(16) uint8_t smem_raw[];
    const uint32_t ring = smem_u32(smem_raw);
    const uint32_t stash = ring + NSLOT * TILE_BYTES;
    const uint32_t bars = stash + 3 * TILE_BYTES;
    const uint32_t full = bars, empty = bars + 32;
    const uint32_t xfull = bars + 64;
    const uint32_t rfull = bars + 144;
    const uint32_t rdone = bars + 288;
    const uint32_t vacant = bars + 336, routed = bars + 344, xgfull = bars + 352, gated = bars + 360;
    const uint32_t soon = bars + 376, qfull = bars + 384, epv = bars + 392, alldone = bars + 400;
    const uint32_t epoch = bars + 368;
    [[maybe_unused]] const uint32_t trbuf = bars + 416;
    const uint32_t ffull = rfull, fempty = rfull + 8 * FSLOT, qdone = rdone, h1done = rdone + 32, wperm = trbuf;

    const int warp = __shfl_sync(0xffffffffu, threadIdx.x >> 5, 0), wg = warp >> 2;
    const int rank = blockIdx.x & 1;
    const int cl = blockIdx.x >> 1;
    const int r7 = ((cl - 36) * 37) >> 8;
    const int qp = cl < 36 ? (cl < 4 ? 0 : (cl - 4) & 7) : cl - 35 - 7 * r7;
    const int grp = cl < 4 ? cl + 4 : cl < 36 ? (cl - 4) >> 3 : r7 + 4;
    const bool helper = blockIdx.x >= N_MAIN;
    const int qt = helper ? (blockIdx.x - N_MAIN) * 4 : qp * 2 + rank;

    auto load_x = [&](int w, int i, int tile) {
        const uint32_t bar = xfull + (w * 5 + i) * 8;
        mbar_expect_tx(bar, 16384);
        tma_3d(ring + (i == 4 ? 2 : 3 + i) * TILE_BYTES + w * 16384, &tm_x, bar, 0, tile * 128 + w * 64, i == 0 ? 8 : 2 * i - 2);
    };
    if (warp == 4) {
        if (elect_one()) {
#pragma unroll
            for (int i = 0; i < 10; i++) mbar_init(xfull + 8 * i, 1);
#pragma unroll
            for (int i = 0; i < XN; i++) load_x(i & 1, i >> 1, qt);
            asm volatile("fence.mbarrier_init.release.cluster;" ::: "memory");
        }
        __syncwarp();
    }
    PT(6);
    if ((ring & 0xFFFFFFu) != RING_OFFSET) return;
    PT(7);
    if (warp >= 5 && elect_one()) {
        if (warp == 5) {
#pragma unroll
            for (int i = 0; i < NSLOT; i++) { mbar_init(full + 8 * i, 1); mbar_init(empty + 8 * i, 16); }
            mbar_arrive(full + 16);
            mbar_arrive(full + 24);
        } else if (warp == 6) {
#pragma unroll
            for (int i = 0; i < 6; i++) mbar_init(rdone + 8 * i, helper ? 8 : 4);
        } else if (warp == 7) {
            mbar_init(vacant, 8); mbar_init(routed, 32); mbar_init(xgfull, 1); mbar_init(gated, 8); mbar_init(soon, 1);
            mbar_init(qfull, 1); mbar_init(epv, 1); mbar_init(alldone, 8);
        } else if (warp == 8) {
            asm volatile("prefetch.tensormap [%0];" ::"l"(&tm_wq) : "memory");
        } else {
#pragma unroll
            for (int i = 0; i < 6; i++) mbar_init(rfull + ((warp - 9) * 6 + i) * 8, helper && warp == 10 ? 4 : 1);
        }
        asm volatile("fence.mbarrier_init.release.cluster;" ::: "memory");
    }
    __syncwarp();
    PT(1);
    asm volatile("barrier.cluster.arrive.relaxed.aligned;" ::: "memory");
    if (warp == 4) {
        if (elect_one()) {
#pragma unroll
            for (int i = XN; i < 10; i++) load_x(i & 1, i >> 1, qt);
        }
        __syncwarp();
    }

    if (wg == 2) {
        asm volatile("setmaxnreg.dec.sync.aligned.u32 24;");
        asm volatile("barrier.cluster.wait.aligned;" ::: "memory");
        uint32_t lane;
        asm volatile("mov.u32 %0, %%laneid;" : "=r"(lane));
        PT(2);
        if (warp == 8 && helper) {
          if (elect_one()) {
#pragma unroll 1
            for (int t = 0; t < 4; t++) {
#pragma unroll 1
                for (int i = 0; i < 20; i++) {
                    const int s = i % 3;
                    mbar_wait(empty + 8 * s, ((t + (i + 1) / 3) & 1) ^ 1);
                    mbar_expect_tx(full + 8 * s, TILE_BYTES);
                    tma_2d_mc(ring + s * TILE_BYTES + rank * 16384, &tm_wq, full + 8 * s, (((i / 5) * 2 + rank) * 4 + 3) * 128 + 64,
                              ((i + 4) % 5) * 128);
                    if (t == 0 && i == 2) {
                        asm volatile("nanosleep.u32 1500;");
#pragma unroll 1
                        for (int k = 3 + ((blockIdx.x >> 1) & 1); k < 20; k += 2) tma_prefetch(&tm_wq, (((k / 5) * 2 + rank) * 4 + 3) * 128 + 64, ((k + 4) % 5) * 128);
                    }
                    if (i == 2 && t < 3) {
#pragma unroll 1
                        for (int k = 2; k < 8; k++) load_x(k & 1, k >> 1, qt + t + 1);
                    }
                    if (i == 18 && t < 3) {
                        mbar_wait(empty + 24, t & 1);
                        load_x(0, 0, qt + t + 1); load_x(1, 0, qt + t + 1);
                    }
                }
                if (t < 3) {
                    mbar_wait(empty + 16, t & 1);
                    mbar_arrive(full + 16);
                    load_x(0, 4, qt + t + 1); load_x(1, 4, qt + t + 1);
                }
            }
            const int e = blockIdx.x - N_MAIN, nb = e == N_MOE - 1 ? 6 : 7, nkt = (nb + 1) >> 1;
            mbar_wait(h1done, 0);
            uint32_t s = 0, ph = 1;
#pragma unroll 1
            for (int o0 = 0, w; o0 < nb + 5; o0 += w) {
                const bool up = o0 < nb;
                w = o0 + 1 < (up ? nb : nb + 5) ? 2 : 1;
#pragma unroll 1
                for (int k = 0; k < (up ? 5 : nkt) * w; k++) {
                    const int o = o0 + (k & (w - 1)), i = k >> (w - 1);
                    mbar_wait(fempty + 8 * s, ph);
                    mbar_expect_tx(ffull + 8 * s, TILE_BYTES);
                    const int c0 = up ? (e * 7 + o) * 64 : (o - nb) * 128, c1 = (up ? 0 : e * 448) + i * 128;
                    tma_2d(ring + s * TILE_BYTES, up ? &tm_g : &tm_d, ffull + 8 * s, c0, c1);
                    tma_2d(ring + s * TILE_BYTES + 16384, up ? &tm_u : &tm_d, ffull + 8 * s, up ? c0 : c0 + 64, c1);
                    if (++s == FSLOT) { s = 0; ph ^= 1; }
                }
            }
          }
        } else if (warp == 8) {
          if (elect_one()) {
            PT(3);
            auto coords = [&](int i, const CUtensorMap*& tm, int& c0, int& c1) {
                c0 = rank * 64;
                if (i < 20) {
                    const int ps = i / 5;
                    tm = &tm_wq; c1 = (i % 5 < 3 ? i % 5 : 7 - i % 5) * 128;
                    if (ps == 1) {
                        c0 = 0;
                        c1 = (i == 5 ? rank : i == 6 ? 2 : 4 - rank) * 128;
                    }
                    c0 += (grp * 4 + (ps < 2 ? 2 + ps : 3 - ps)) * 128;
                } else if (i < 148) {
                    const int u = i - 20;
                    const bool isk = (u == 0) || ((u & 1) && u != 127);
                    const int b = isk ? (u + 1) >> 1 : (u == 127 ? 63 : (u >> 1) - 1);
                    tm = isk ? &tm_k : &tm_v; c1 = (grp * 64 + b) * 128;
                } else {
                    tm = &tm_wo; c0 = (i < 152 ? ((i - 132) >> 1) ^ (grp >> 2) : (grp + ((i - 150) >> 1)) & 7) * 64; c1 = (grp * 4 + (i & 1) * 2 + rank) * 128;
                }
            };
#pragma unroll 1
            for (int i = 0; i < 168; i++) {
                const CUtensorMap* tm;
                int c0, c1;
                if (i == 8) i = 10;
                const int a = i < 8 ? i : i - 2;
                const int s = i < 20 ? a % 3 : (i & 3);
                const uint32_t ph = i < 20 ? ((a + 1) / 3) & 1 : ((i >> 2) & 1) ^ (s < 2);
                coords(i, tm, c0, c1);
                if (i == QAT) mbar_wait(qfull, 0);
                mbar_wait(empty + 8 * s, ph ^ 1);
                if (i == 6) {
                    mbar_expect_tx(full + 8 * s, TILE_BYTES / 2);
                    if (rank == 0) tma_2d_mc(ring + s * TILE_BYTES, tm, full + 8 * s, c0, c1);
                } else {
                    mbar_expect_tx(full + 8 * s, TILE_BYTES);
                    tma_2d_mc(ring + s * TILE_BYTES + rank * 16384, tm, full + 8 * s, c0, c1);
                }
                if (i == 140) mbar_arrive(soon);
                if (i >= 163 && i < 167) {
                    if (i == 163) {
                        TL(0);
                        mbar_wait(routed, 0);
                        asm volatile("fence.proxy.async.global;" ::: "memory");
                        TL(1);
                        mbar_expect_tx(xgfull, TILE_BYTES);
                    }
                    asm volatile("cp.async.bulk.shared::cluster.global.mbarrier::complete_tx::bytes [%0], [%1], 8192, [%2];"
                                 ::"r"(stash + 3 * 16384 + (i - 163) * 8192), "l"(sc->gate + blockIdx.x * 2560 + (i - 163) * 512), "r"(xgfull) : "memory");
                }
                if (i == 12) asm volatile("prefetch.tensormap [%0];\nprefetch.tensormap [%1];" ::"l"(&tm_k), "l"(&tm_v) : "memory");
                if (i == 140) asm volatile("prefetch.tensormap [%0];" ::"l"(&tm_wo) : "memory");
                if (i >= GPF && i < GPF + 10)
                    asm volatile("cp.async.bulk.prefetch.L2.global [%0], 4096;" ::"l"(sc->gate + blockIdx.x * 2560 + (i - GPF) * 256) : "memory");
                const int j = i < 2 ? 2 + i : i == 2 ? 4 + ((qp - 4) & 7) : i + 9;
                if (j < 168 && (j & 7) == qp && (j & ~1) != 8) {
                    coords(j, tm, c0, c1);
                    tma_prefetch(tm, c0, c1);
                }
            }
            sc->epoch[blockIdx.x] += 1;
          }
        } else if (warp == 9) {
            const uint32_t ep = sc->epoch[blockIdx.x] + 1;
            if (helper) {
#pragma unroll 1
                for (int t = 0; t < 4; t++) {
                    if (t == 3) {
                        mbar_wait_sleep(qdone + 40, 0);
                        if (lane == 0) flag_set(sc->flag_r + (blockIdx.x - N_MAIN), ep);
                    }
                    mbar_wait_sleep(qdone + 8 * t, 0);
                    if (lane == 0) flag_set(sc->flag_q + qt + t, ep);
                }
                if (lane == 0) sc->epoch[blockIdx.x] = ep;
            } else {
                mbar_wait_sleep(gated, 0);
                flag_wait_bounded<300>(sc->flag_q + qt, ep);
                asm volatile("fence.proxy.async.global;" ::: "memory");
                if (lane == 0) mbar_expect_tx(qfull, 16384);
                __syncwarp();
                if (lane < 8)
                    asm volatile("cp.async.bulk.shared::cluster.global.mbarrier::complete_tx::bytes [%0], [%1], 2048, [%2];"
                                 ::"r"(stash + 2 * TILE_BYTES + lane * 4096 + 2048),
                                   "l"(sc->qoff + ((qt * 4 + (grp >> 1)) * 8 + lane) * 256 + (grp & 1) * 128), "r"(qfull) : "memory");
            }
            mbar_wait_bounded(alldone, 0);
        } else if (helper) {
        } else if (warp == 10) {
            const uint32_t ep = sc->epoch[blockIdx.x] + 1;
            if (lane == 0) {
                asm volatile("st.shared.u32 [%0], %1;" ::"r"(epoch), "r"(ep) : "memory");
                mbar_arrive(epv);
            }
            mbar_wait_sleep(gated, 0);
            flag_wait<400>(sc->flag_u + (lane & 3), ep);
            __syncwarp();
            const int rrow = __ldcg(sc->idx + (lane & 7));
            uint32_t hit = __ballot_sync(0xffffffffu, lane < 8 && (rrow >> 7) == qt);
            while (hit) {
                const int k = __ffs(hit) - 1, row = __shfl_sync(0xffffffffu, rrow, k);
                hit &= hit - 1;
#pragma unroll 1
                for (int i = lane; i < 40; i += 32) {
                    const int th = ((row >> 4) & 7) * 32 + (row & 7) * 4 + (i & 3);
                    ((uint32_t*)sc->gate)[(((blockIdx.x * 5 + (i >> 3)) * 2 + 1) * 256 + th) * 4 + ((i >> 1) & 2) + ((row >> 3) & 1)] =
                        __ldcg((const uint32_t*)sc->routed + k * (DM / 2) + (i < 32 ? grp * 32 + i : 224 + grp * 8 + i));
                }
            }
            mbar_arrive(routed);
        } else if (warp == 11) {
            const uint32_t ep = sc->epoch[blockIdx.x] + 1;
            const uint32_t unit = lane < 16 ? lane >> 3 : (lane >> 1) - 6;
            const uint32_t ofs = (lane & 1) * 8192 + (lane < 16 ? ((lane >> 1) & 3) * 2048 : 0);
            if (lane < 18) mbar_expect_tx(rfull + 8 * lane, 8192);
            mbar_wait_sleep(soon, 0);
            uint32_t done = lane >= 30;
            do {
                if (!done) {
                    uint4 v;
                    asm volatile("ld.relaxed.gpu.global.v4.u32 {%0, %1, %2, %3}, [%4];" : "=r"(v.x), "=r"(v.y), "=r"(v.z), "=r"(v.w)
                                 : "l"(sc->flag + (qt * 8 + grp) * 32 + lane) : "memory");
                    uint32_t ok = v.x == ep && v.y == ep && v.z == ep && v.w == ep;
                    if (ok)
                        asm volatile("{\n.reg .pred p;\nmbarrier.test_wait.parity.shared::cta.b64 p, [%1], 0;\nselp.u32 %0, 1, 0, p;\n}\n"
                                     : "=r"(ok) : "r"(unit >= 6 ? rdone + (lane - 24) * 8 : vacant) : "memory");
                    done = ok;
                    if (ok)
                        asm volatile("cp.async.bulk.shared::cluster.global.mbarrier::complete_tx::bytes [%0], [%1], %2, [%3];"
                                     ::"r"(stash + (unit >= 6 ? unit - 6 : unit) * 16384 + ofs),
                                       "l"((const char*)sc->part + ((qt * 8 + grp) * 9 + unit) * 16384 + ofs), "r"(lane < 16 ? 2048 : 8192),
                                       "r"(rfull + 16 * unit + 8 * (lane & 1)) : "memory");
                }
            } while (!__all_sync(0xffffffffu, done));
        }
    } else {
        asm volatile("setmaxnreg.inc.sync.aligned.u32 240;");
        const uint32_t lane = threadIdx.x & 31;
        PT(2);
        asm volatile("barrier.cluster.wait.aligned;" ::: "memory");
        PT(3);
        const int my_bar = 1 + wg, other_bar = 2 - wg;
        const uint32_t my_stash = stash + warp * 4096 + lane * 16;
        constexpr uint32_t T16 = TILE_BYTES / 16;
        constexpr uint32_t ring16 = RING_OFFSET >> 4;
        uint32_t rel = 0;
        if (lane < 2)
            asm("mapa.shared::cluster.u32 %0, %1, %2;" : "=r"(rel) : "r"(empty), "r"(lane));
        rel = opaque(rel);

        const int zero = gridDim.y - 1;
        PT(4);

        uint32_t q[32];
        float acc[64];
        float wsum;
        uint32_t ep_tag;
        uint2 st0, st1;
        auto project = [&](auto helper_c, int job) {
            constexpr bool HELPER = decltype(helper_c)::value;
            float (&acc32)[32] = *reinterpret_cast<float (*)[32]>(&acc[0]);
            const int tile = qt + job;
            uint32_t lane = threadIdx.x & 31;
            if (HELPER) asm volatile("mov.u32 %0, %%laneid;" : "=r"(lane));
            uint32_t xa[128];
            const uint32_t lm_off = wg * 16384 + ((warp & 3) * 16 + (lane & 15)) * 128 + (((lane >> 4) ^ (lane & 7)) << 4);
            float sm[4][4] = {}, sq[4][4] = {};
            constexpr uint32_t ONES = 0x3f803f80u;
            constexpr float SC = 0.08838834764831845f * 1.4426950408889634f;
            auto squares = [&](const uint32_t* a) {
#pragma unroll
                for (int r = 0; r < 4; r++) hmma8(sq[r], a[r & 2], a[(r & 2) + 1], a[r]);
            };
            const int row = tile * 128 + warp * 16 + (lane >> 2);
            auto load_stats = [&](int t) {
                asm volatile("ld.relaxed.gpu.global.v2.u32 {%0, %1}, [%4];\nld.relaxed.gpu.global.v2.u32 {%2, %3}, [%4 + 64];"
                             : "=r"(st0.x), "=r"(st0.y), "=r"(st1.x), "=r"(st1.y) : "l"(sc->stat + t * 128 + warp * 16 + (lane >> 2)) : "memory");
            };
            uint32_t mm0, mm1;
            float rd0, rd1;
            if (HELPER && job == 0) load_stats(tile);
#pragma unroll
            for (int i = 0; i < 5; i++) {
                mbar_wait(xfull + (wg * 5 + i) * 8, HELPER ? job & 1 : 0);
                if (i == 0) PT(5);
                if (HELPER && i == 0) TR(20 + job * 8);
                if (HELPER && i == 4) TR(20 + job * 8 + 7);
                if (HELPER && job == 1) TR(110 + i);
                const uint32_t base = ring + (i == 4 ? 2 : 3 + i) * TILE_BYTES + lm_off;
                uint32_t* a = xa + (i == 0 ? 96 : 32 * (i - 1));
#pragma unroll
                for (int ks = 0; ks < 8; ks++)
                    ldsm4((base ^ ((ks & 3) << 5)) + (ks >> 2) * 8192, a[4 * ks], a[4 * ks + 1], a[4 * ks + 2], a[4 * ks + 3]);
                if (i == 4) PT(9);
                uint32_t wb[16];
#pragma unroll
                for (int ks = 0; ks < 8; ks++) {
                    wb[2 * ks] = ONES; wb[2 * ks + 1] = ONES;
                    if (HELPER)
                        asm volatile("ld.shared.v2.u32 {%0, %1}, [%2];" : "=r"(wb[2 * ks]), "=r"(wb[2 * ks + 1]) : "r"(wperm + (lane & 3) * 8 + ((i == 0 ? 32 : 8 * i - 8) + ks) * 32));
                }
#pragma unroll
                for (int ks = 0; ks < 8; ks++) {
                    hmma(sm[ks & 3], a[4 * ks], a[4 * ks + 1], a[4 * ks + 2], a[4 * ks + 3], wb[2 * ks], wb[2 * ks + 1]);
                    if (!HELPER && i < 4) squares(a + 4 * ks);
                }
                if (HELPER && i == 0) {
                    while (__any_sync(0xffffffffu, ((st0.x ^ ep_tag) | (st1.x ^ ep_tag)) >> 16)) load_stats(tile);
                    mm0 = __byte_perm(st0.x, 0, 0x1010); mm1 = __byte_perm(st1.x, 0, 0x1010);
#pragma unroll
                    for (int ks = 0; ks < 8; ks++)
                        stsm4((base ^ ((ks & 3) << 5)) + (ks >> 2) * 8192, bf2_sub(a[4 * ks], mm0), bf2_sub(a[4 * ks + 1], mm1),
                              bf2_sub(a[4 * ks + 2], mm0), bf2_sub(a[4 * ks + 3], mm1));
                    asm volatile("fence.proxy.async.shared::cta;" ::: "memory");
                }
            }
            release_at<16>(rel);
            sched_fence(zero);
            const float m0 = ((sm[0][0] + sm[1][0]) + (sm[2][0] + sm[3][0])) * (HELPER ? 1.f : 1.f / DM);
            const float m1 = ((sm[0][2] + sm[1][2]) + (sm[2][2] + sm[3][2])) * (HELPER ? 1.f : 1.f / DM);
            if (HELPER) {
                const float id0 = __uint_as_float(st0.y), id1 = __uint_as_float(st1.y);
                rd0 = SC * id0; rd1 = SC * id1;
                if ((lane & 3) == 0) {
                    sc->r[row] = bf_round((m0 - bf_lo(mm0) * wsum) * id0);
                    sc->r[row + 8] = bf_round((m1 - bf_lo(mm1) * wsum) * id1);
                }
                __syncwarp();
                if (job == 3 && lane == 0) mbar_arrive(qdone + 40);
            } else {
                mm0 = pack_bf16(m0, m0); mm1 = pack_bf16(m1, m1);
            }
            auto centre = [&](int kt) {
#pragma unroll
                for (int i = 32 * kt; i < 32 * kt + 32; i++) asm volatile("sub.rn.bf16x2 %0, %0, %1;" : "+r"(xa[i]) : "r"((i & 1) ? mm1 : mm0));
            };
            if (EARLYA == 1 && !HELPER && wg == 1) bar_arrive(1);
            if (!HELPER) {
#pragma unroll
                for (int ks = 0; ks < 8; ks++) squares(xa + 96 + 4 * ks);
            }
            if (EARLYA == 2 && !HELPER && wg == 1) bar_arrive(1);
            if (!HELPER) centre(0);
            if ((EARLYA == 0 || HELPER) && wg == 1) bar_arrive(1);
            auto diag = [&](int r, int h) { return (lane & 4) ? sq[r][h + 1] + sq[r + 2][h + 1] : sq[r][h] + sq[r + 2][h]; };
            auto spread = [&](float v) { return __shfl_sync(0xffffffffu, v, (lane & ~3u) | (lane >> 3)) * (1.f / DM); };
            if (!HELPER) { rd0 = diag(0, 0); rd1 = diag(1, 2); }
            PT(10);

            if (HELPER) TR(20 + job * 8 + 1);
            uint32_t qs = 0, qph = HELPER ? job & 1 : 0;
            uint4 gx;
            if (HELPER) {
#pragma unroll
                for (int i = 0; i < 64; i++) acc[i] = 0.f;
            }
            const uint32_t xs16 = ring16 + 3 * T16 + wg * 1024;
            constexpr int SS = HELPER ? 0 : 3;
            auto finish_stats = [&] {
                float v0 = spread(rd0) - m0 * m0, v1 = spread(rd1) - m1 * m1;
                if (__any_sync(0xffffffffu, !(m0 * m0 <= 256.f * v0 && m1 * m1 <= 256.f * v1))) {
                    const uint4* xr = (const uint4*)x + row * (DM / 8) + (lane & 3);
                    v0 = 0.f; v1 = 0.f;
#pragma unroll 1
                    for (int i = 0; i < DM / 32; i++) {
                        const uint4 a = __ldg(xr + 4 * i), b = __ldg(xr + DM + 4 * i);
                        const uint32_t w[8] = {a.x, a.y, a.z, a.w, b.x, b.y, b.z, b.w};
#pragma unroll
                        for (int k = 0; k < 8; k++) {
                            const uint32_t d = bf2_sub(w[k], k < 4 ? mm0 : mm1);
                            float& v = k < 4 ? v0 : v1;
                            v = fmaf(bf_lo(d), bf_lo(d), fmaf(bf_hi(d), bf_hi(d), v));
                        }
                    }
#pragma unroll
                    for (int d = 1; d <= 2; d <<= 1) { v0 += __shfl_xor_sync(0xffffffffu, v0, d); v1 += __shfl_xor_sync(0xffffffffu, v1, d); }
                    v0 *= 1.f / DM; v1 *= 1.f / DM;
                    const float e0 = m0 - bf_lo(mm0), e1 = m1 - bf_lo(mm1);
                    v0 -= e0 * e0; v1 -= e1 * e1;
                }
                const float id0 = inv_den(fmaxf(v0, 0.f)), id1 = inv_den(fmaxf(v1, 0.f));
                rd0 = SC * id0; rd1 = SC * id1;
                if (warp == grp) {
                    mbar_wait(epv, 0);
                    uint32_t tg;
                    asm volatile("ld.shared.u32 %0, [%1];" : "=r"(tg) : "r"(epoch));
                    if ((lane & 3) == 0)
                        asm volatile("st.relaxed.gpu.global.v2.u32 [%0], {%1, %2};\nst.relaxed.gpu.global.v2.u32 [%0 + 64], {%3, %4};"
                                     ::"l"(sc->stat + row), "r"(__byte_perm(mm0, tg, 0x5410)), "f"(id0), "r"(__byte_perm(mm1, tg, 0x5410)), "f"(id1) : "memory");
                }
            };
#pragma unroll 1
            for (int pass = 0;; pass++) {
                const uint32_t hs = my_stash + (pass == 2 ? 0 : pass + 1) * TILE_BYTES;
                uint4* const dst = sc->qoff + ((tile * 4 + pass) * 8 + warp) * 256 + lane;
                auto put = [&](int lo) {
#pragma unroll
                    for (int i = lo; i < lo + 4; i++) {
                        const uint4 v = make_uint4(pack_bf16(acc[8 * i] * rd0, acc[8 * i + 1] * rd0), pack_bf16(acc[8 * i + 2] * rd1, acc[8 * i + 3] * rd1),
                                                   pack_bf16(acc[8 * i + 4] * rd0, acc[8 * i + 5] * rd0), pack_bf16(acc[8 * i + 6] * rd1, acc[8 * i + 7] * rd1));
                        if (HELPER) dst[i * 32] = v;
                        else sts128(hs + i * 512, v.x, v.y, v.z, v.w);
                        if (PUTF == 0 ? (i == 2 || i == 5) : PUTF == 1 ? (i == 3) : PUTF == 2 ? (i & 1) : false) sched_fence(zero);
                    }
                };
                auto gate_load = [&](int j) {
                    const uint32_t* src = (const uint32_t*)x + (qt * 128 + warp * 16 + (lane >> 2)) * (DM / 2) + (lane & 3) +
                                          (j < 4 ? grp * 32 + j * 8 : 256 + grp * 8);
                    asm volatile("ld.global.nc.u32 %0, [%4];\nld.global.nc.u32 %1, [%4 + %5];\n"
                                 "ld.global.nc.u32 %2, [%4 + 16];\nld.global.nc.u32 %3, [%4 + %5 + 16];"
                                 : "=r"(gx.x), "=r"(gx.y), "=r"(gx.z), "=r"(gx.w) : "l"(src), "n"(8 * DM * 2));
                };
                auto gate_store = [&](int j) {
                    const float id0 = rd0 * (1.f / SC), id1 = rd1 * (1.f / SC);
                    uint4* g = sc->gate + (blockIdx.x * 5 + j) * 512 + threadIdx.x;
                    g[0] = gx;
                    g[256] = make_uint4(silu2_ln(normalise(gx.x, mm0, id0)), silu2_ln(normalise(gx.y, mm1, id1)),
                                        silu2_ln(normalise(gx.z, mm0, id0)), silu2_ln(normalise(gx.w, mm1, id1)));
                };
                auto advance = [&] {
                    const uint32_t r = rel ? rel + 8 * qs : 0;
                    if (++qs == 2) qph ^= 1;
                    if (qs == 3) qs = 0;
                    return r;
                };
                if (!HELPER && pass == 1) {
#pragma unroll
                    for (int turn = 0; turn < 3; turn++) {
                        if (turn) mbar_wait(full + 8 * qs, qph);
                        bar_sync(my_bar);
                        const uint32_t tile16 = ring16 + qs * T16;
                        wg_fence();
#pragma unroll
                        for (int ks = 0; ks < (turn == 1 ? 8 : 16); ks++) {
                            const uint32_t* a = xa + (turn == 2 ? 64 : turn * 64) + 4 * ks;
                            if (turn == 2 && ks < 8) wgmma_ss64(acc32, desc_kmajor(xs16 - (ks >> 2) * 512, ks), desc_nmajor(tile16, ks), 1);
                            else wgmma_rs64(acc32, a[0], a[1], a[2], a[3], desc_nmajor(tile16, ks), turn || ks);
                        }
                        wg_commit();
                        bar_arrive(other_bar);
                        const uint32_t rl = advance();
                        if (turn == 2) mbar_wait(full + 8 * qs, qph);
                        wg_wait<0>();
                        TA(5 + 2 * turn);
                        release_at<0>(rl);
                    }
                    pin(acc32);
                    put(0);
                    continue;
                }
                uint32_t rl = 0;
#pragma unroll
                for (int kt = 0; kt < 5; kt++) {
                    const bool takes = !HELPER || kt == 0 || kt == 2 || kt == 3, passes = !HELPER || kt == 1 || kt == 2 || kt == 4;
                    if (kt != 0 || pass == 0) mbar_wait(full + 8 * qs, qph);
                    if (takes) bar_sync(my_bar);
                    const uint32_t tile16 = ring16 + qs * T16;
                    wg_fence();
                    if (kt != SS) {
                        mma_tile<1>(acc, xa + (kt < SS ? kt : kt - 1) * 32, tile16, kt != 0);
                    } else {
#pragma unroll
                        for (int ks = 0; ks < 8; ks++) wgmma_ss(acc, desc_kmajor(xs16 - (ks >> 2) * 512, ks), desc_nmajor(tile16, ks), kt || ks);
                        wg_commit();
                    }
                    if (passes && !(HELPER && kt == 4 && pass == 3 && wg == 1)) bar_arrive(other_bar);
                    if (HELPER && pass == 0 && kt < 4) centre(kt);
                    if (!HELPER && pass == 0 && kt < 3) {
#pragma unroll
                        for (int ks = 3 * kt; ks < 3 * kt + 3 && ks < 8; ks++) {
                            const uint32_t ad = ((ring + 3 * TILE_BYTES + lm_off) ^ ((ks & 3) << 5)) + (ks >> 2) * 8192;
                            uint32_t a, b, c, d;
                            ldsm4(ad, a, b, c, d);
                            stsm4(ad, bf2_sub(a, mm0), bf2_sub(b, mm1), bf2_sub(c, mm0), bf2_sub(d, mm1));
                        }
                        if (kt == 2) asm volatile("fence.proxy.async.shared::cta;" ::: "memory");
                    }
                    if (!HELPER && pass == 0 && kt == FINK) finish_stats();
                    if (HELPER && kt == 2 && pass == 3 && job < 3) load_stats(tile + 1);
                    if (!HELPER && pass >= 2 && kt < 4) {
                        if (kt & 1) gate_store((pass - 2) * 2 + (kt >> 1));
                        else gate_load((pass - 2) * 2 + (kt >> 1));
                    }
                    if (!HELPER && pass == G4 && kt == 3) gate_load(4);
                    if (!HELPER && pass == G4 && kt == 4) gate_store(4);
                    const uint32_t rl_prev = rl;
                    rl = advance();
                    if (!passes) continue;
                    if (HELPER && kt != 2) {
                        wg_wait<1>();
                        if (job == 1) TR(120 + pass * 5 + kt - 1);
                        release_at<0>(rl_prev);
                        if (kt == 1 && pass == 3) release_at<24>(rel);
                    }
                    if (kt == 4 && !(HELPER && pass == 3)) mbar_wait(full + 8 * qs, qph);
                    wg_wait<0>();
                    if (!HELPER) TA(pass * 5 + kt);
                    if (HELPER && job == 1) TR(120 + pass * 5 + kt);
                    release_at<0>(rl);
                    if (!HELPER && kt < 3 && pass == 0) centre(kt + 1);
                }
                pin(acc);
                if (!HELPER && pass == 3) break;
                put(0);
                put(4);
                if (HELPER) TR(20 + job * 8 + 2 + pass);
                if (HELPER && pass == 3) {
                    __syncwarp();
                    if (lane == 0) mbar_arrive(qdone + 8 * job);
                    return;
                }
            }
            release_at<24>(rel);
            if (lane == 0) mbar_arrive(gated);
#pragma unroll
            for (int i = 0; i < 32; i++) {
                const float r = (i & 1) ? rd1 : rd0;
                q[i] = pack_bf16(acc[2 * i] * r, acc[2 * i + 1] * r);
            }
        };
        if (helper) {
            const uint32_t ep = sc->epoch[blockIdx.x] + 1;
            if (threadIdx.x < 160) {
                const uint32_t* w32 = (const uint32_t*)wr + (threadIdx.x >> 2) * 8 + (threadIdx.x & 3);
                asm volatile("st.shared.v2.u32 [%0], {%1, %2};" ::"r"(wperm + threadIdx.x * 8), "r"(__ldg(w32)), "r"(__ldg(w32 + 4)) : "memory");
            }
            asm volatile("bar.sync 3, 256;" ::: "memory");
            float ws[4] = {};
#pragma unroll 4
            for (int ks = 0; ks < 40; ks++) {
                uint32_t b0, b1;
                asm volatile("ld.shared.v2.u32 {%0, %1}, [%2];" : "=r"(b0), "=r"(b1) : "r"(wperm + (lane & 3) * 8 + ks * 32));
                hmma(ws, 0x3f803f80u, 0x3f803f80u, 0x3f803f80u, 0x3f803f80u, b0, b1);
            }
            wsum = ws[0];
            ep_tag = ep << 16;
            TR(0);
#pragma unroll 1
            for (int job = 0; job < 4; job++) {
                project(cint<1>(), job);
                TR(1 + job);
            }
            if (elect_one()) mbar_arrive(h1done);
            ffn_role(sc, ring, ffull, fempty, alldone, blockIdx.x - N_MAIN, ep, warp, x);
            return;
        }
        project(cint<0>(), 0);
        TRM(2);
        TG(112);

        float o[64];
        uint32_t p[32];
        float l0, l1;
        constexpr float L_LO = 9.313225746154785e-10f, L_HI = 1.152921504606847e18f;
        float l_hi = L_HI;
        float (&s)[64] = acc;

        auto exp_range = [&](const float (&s)[64], int lo, int hi, float& u0, float& u1) {
            float w0 = 0.f, w1 = 0.f;
#pragma unroll
            for (int i = lo; i < hi; i += 4) {
                const float e0 = ex2(s[i]), e1 = ex2(s[i + 1]), e2 = ex2(s[i + 2]), e3 = ex2(s[i + 3]);
                u0 += e0; u1 += e2;
                if (i == lo) { w0 = e1; w1 = e3; } else { w0 += e1; w1 += e3; }
                p[i / 2] = pack_bf16(e0, e1); p[i / 2 + 1] = pack_bf16(e2, e3);
            }
            u0 += w0; u1 += w1;
        };
        auto unsafe = [&](bool first, float u0, float u1) {
            return (bool)__any_sync(0xffffffffu, !(u0 + u1 <= l_hi) || (first && !(fminf(u0, u1) >= L_LO)));
        };
        auto softmax_true_max = [&](const float (&s)[64], bool first, float b0, float b1, float& u0, float& u1) {
            uint32_t t;
            asm volatile("mov.u32 %0, %%tid.x;" : "=r"(t));
            uint4* const st = sc->rare + blockIdx.x * (17 * 256) + t;
            auto ld = [](const uint4* a) {
                uint4 v;
                asm volatile("ld.global.v4.u32 {%0, %1, %2, %3}, [%4];" : "=r"(v.x), "=r"(v.y), "=r"(v.z), "=r"(v.w) : "l"(a) : "memory");
                return v;
            };
#pragma unroll
            for (int i = 0; i < 16; i++)
                asm volatile("st.global.v4.f32 [%0], {%1, %2, %3, %4};" ::"l"(st + i * 256), "f"(s[4 * i]), "f"(s[4 * i + 1]), "f"(s[4 * i + 2]), "f"(s[4 * i + 3]) : "memory");
            float a0 = s[0], a1 = s[2];
#pragma unroll 1
            for (int i = 0; i < 16; i++) {
                const uint4 v = ld(st + i * 256);
                a0 = fmaxf(a0, fmaxf(__uint_as_float(v.x), __uint_as_float(v.y)));
                a1 = fmaxf(a1, fmaxf(__uint_as_float(v.z), __uint_as_float(v.w)));
            }
            float t0 = b0, t1 = b1, sg0 = 0.f, sg1 = 0.f;
            if (l_hi < 0.f) {
                const uint4 v = ld(st + 16 * 256);
                sg0 = __uint_as_float(v.x); sg1 = __uint_as_float(v.y);
            }
#pragma unroll
            for (int d = 1; d <= 2; d <<= 1) {
                a0 = fmaxf(a0, __shfl_xor_sync(0xffffffffu, a0, d)); a1 = fmaxf(a1, __shfl_xor_sync(0xffffffffu, a1, d));
                t0 += __shfl_xor_sync(0xffffffffu, t0, d); t1 += __shfl_xor_sync(0xffffffffu, t1, d);
            }
            if (!first) {
                a0 = fmaxf(a0, l_hi < 0.f ? sg0 : __log2f(t0)); a1 = fmaxf(a1, l_hi < 0.f ? sg1 : __log2f(t1));
            }
            const float al0 = first ? 1.f : ex2(sg0 - a0), al1 = first ? 1.f : ex2(sg1 - a1);
            asm volatile("st.global.v2.f32 [%0], {%1, %2};" ::"l"(st + 16 * 256), "f"(a0), "f"(a1) : "memory");
            l_hi = -1.f;
            u0 = b0 * al0; u1 = b1 * al1;
#pragma unroll 1
            for (int i = 0; i < 16; i++) {
                const uint4 v = ld(st + i * 256);
                const float e0 = ex2(__uint_as_float(v.x) - a0), e1 = ex2(__uint_as_float(v.y) - a0);
                const float e2 = ex2(__uint_as_float(v.z) - a1), e3 = ex2(__uint_as_float(v.w) - a1);
                u0 += e0 + e1; u1 += e2 + e3;
                asm volatile("st.global.v2.u32 [%0], {%1, %2};" ::"l"((uint2*)(st + (i >> 1) * 256) + (i & 1)), "r"(pack_bf16(e0, e1)), "r"(pack_bf16(e2, e3)) : "memory");
            }
#pragma unroll
            for (int i = 0; i < 8; i++) {
                const uint4 v = ld(st + i * 256);
                p[4 * i] = v.x; p[4 * i + 1] = v.y; p[4 * i + 2] = v.z; p[4 * i + 3] = v.w;
            }
            if (&s != &o) {
#pragma unroll
                for (int i = 0; i < 64; i++) o[i] *= (i & 2) ? al1 : al0;
            }
        };
        auto inv_sums = [&](float& i0, float& i1) {
            float a = l0, b = l1;
            a += __shfl_xor_sync(0xffffffffu, a, 1); b += __shfl_xor_sync(0xffffffffu, b, 1);
            a += __shfl_xor_sync(0xffffffffu, a, 2); b += __shfl_xor_sync(0xffffffffu, b, 2);
            i0 = rcp(a); i1 = rcp(b);
        };

        {
            bar_sync(my_bar);
            wg_fence();
            mma_tile<0>(o, q, ring16, 0);
            mbar_wait(full + 8, 0);
            wg_fence();
            mma_tile<0>(s, q, ring16 + T16, 0);
            bar_arrive(other_bar);
            wg_wait<1>();
            TA(20);
            release_at<0>(rel);
            pin(o);
            l0 = 0.f; l1 = 0.f;
            exp_range(o, 0, 64, l0, l1);
            mbar_wait(full + 16, 1);
            wg_wait<0>();
            if (unsafe(true, l0, l1)) softmax_true_max(o, true, 0.f, 0.f, l0, l1);
        }
        uint32_t qsrc = my_stash;
        float il0 = 0.f, il1 = 0.f;
        auto step = [&](auto odd_c, int m) {
            constexpr int ODD = decltype(odd_c)::value;
            constexpr int KS = ODD ? 3 : 1, VS = ODD ? 0 : 2;
            [[maybe_unused]] const int it = 2 * m + ODD;
            const uint32_t ph = m & 1;
            TC(0);
            bar_sync(my_bar);
            TC(1);
            if (ODD || m) {
                wg_fence();
                mma_tile<0>(s, q, ring16 + KS * T16, 0);
            }
            TC(2);
            if (!ODD) {
                if ((m & 7) == 0 && m) {
#pragma unroll
                    for (int i = FSPLIT; i < 8; i++)
                        sts128(qsrc + i * 512,
                               pack_bf16(o[8 * i] * il0, o[8 * i + 1] * il0), pack_bf16(o[8 * i + 2] * il1, o[8 * i + 3] * il1),
                               pack_bf16(o[8 * i + 4] * il0, o[8 * i + 5] * il0), pack_bf16(o[8 * i + 6] * il1, o[8 * i + 7] * il1));
                    qsrc += m == 24 ? -2 * TILE_BYTES : TILE_BYTES;
                }
                wg_fence();
            }
#pragma unroll
            for (int ks = 0; ks < 8; ks++) {
                wgmma_rs<1>(o, p[4 * ks], p[4 * ks + 1], p[4 * ks + 2], p[4 * ks + 3], desc_nmajor(ring16 + VS * T16, ks),
                            (ks == 0 && !ODD) ? ((m & 7) != 0) : 1);
                if (ks == SPLIT / 8 - 1 || ks == 7) wg_commit();
            }
            TC(3);
            bar_arrive(other_bar);
            const bool last = ODD && (m & 7) == 7;
            if (last) {
                inv_sums(il0, il1);
                l0 = 0.f; l1 = 0.f; l_hi = L_HI;
            }
            wg_wait<1>();
            TA(21 + it);
            TC(4);
            release_at<8 * KS>(rel);
            const bool newq = (m & 7) == 7;
            if (!ODD) {
                lds128_if<0>(newq, qsrc, q[0], q[1], q[2], q[3]);
                lds128_if<512>(newq, qsrc, q[4], q[5], q[6], q[7]);
                if (QB != 1) lds128_if<1024>(newq, qsrc, q[8], q[9], q[10], q[11]);
            }
            pin(s);
            float u0 = l0, u1 = l1;
            exp_range(s, 0, SPLIT, u0, u1);
            mbar_wait_hot(full + 8 * (KS ^ 2), ph ^ 1);
            if (!ODD) {
                if (QB == 1) lds128_if<1024>(newq, qsrc, q[8], q[9], q[10], q[11]);
                lds128_if<1536>(newq, qsrc, q[12], q[13], q[14], q[15]);
                lds128_if<2048>(newq, qsrc, q[16], q[17], q[18], q[19]);
                if (QB == 2) lds128_if<2560>(newq, qsrc, q[20], q[21], q[22], q[23]);
            }
            TC(5);
            wg_wait<0>();
            release_at<8 * VS>(rel);
            pin(o);
            exp_range(s, SPLIT, 64, u0, u1);
            TC(6);
            mbar_wait_hot(full + 8 * (VS ^ 2), ODD ? ph : ph ^ 1);
            if (!ODD) {
                if (QB != 2) lds128_if<2560>(newq, qsrc, q[20], q[21], q[22], q[23]);
                lds128_if<3072>(newq, qsrc, q[24], q[25], q[26], q[27]);
                lds128_if<3584>(newq, qsrc, q[28], q[29], q[30], q[31]);
            } else if (last) {
#pragma unroll
                for (int i = 0; i < FSPLIT; i++)
                    sts128(qsrc + i * 512,
                           pack_bf16(o[8 * i] * il0, o[8 * i + 1] * il0), pack_bf16(o[8 * i + 2] * il1, o[8 * i + 3] * il1),
                           pack_bf16(o[8 * i + 4] * il0, o[8 * i + 5] * il0), pack_bf16(o[8 * i + 6] * il1, o[8 * i + 7] * il1));
            }
            if (unsafe(last, u0, u1)) softmax_true_max(s, last, l0, l1, u0, u1);
            l0 = u0; l1 = u1;
            TC(7);
            TF(3 + it);
        };
#pragma unroll 1
        for (int m = 0;; m++) {
            step(cint<0>(), m);
            if (m == 31) break;
            step(cint<1>(), m);
        }
        uint32_t ob[64];
        const uint32_t t128 = threadIdx.x & 127;
        uint32_t ep, tag;
        const uint32_t half = 0x8000u;
        auto send = [&](uint4* dst, const float* a) {
            asm volatile("st.relaxed.gpu.global.v4.u32 [%0], {%1, %2, %3, %4};" ::"l"(dst), "r"(lop3<0xD8>(pack_bf16(a[0], a[1]), tag, 0x10000u)),
                         "r"(pack_bf16(a[2], a[3])), "r"(pack_bf16(a[4], a[5])), "r"(pack_bf16(a[6], a[7])) : "memory");
        };
        auto hint = [&](int dst, int job) {
            asm volatile("st.relaxed.gpu.global.u32 [%0], %1;" ::"l"((uint32_t*)(sc->flag + (qt * 8 + dst) * 32 + job) + (warp & 3)), "r"(ep) : "memory");
        };
        float a32[32], own[32];
        auto half_mma = [&](const uint32_t* a, const uint32_t* b, uint32_t t16, int accumulate) {
            wg_fence();
#pragma unroll
            for (int ks = 0; ks < 8; ks++) wgmma_rs64(a32, a[4 * ks], a[4 * ks + 1], a[4 * ks + 2], a[4 * ks + 3], desc_nmajor(t16, ks), ks ? 1 : accumulate);
#pragma unroll
            for (int ks = 0; ks < 8; ks++) wgmma_rs64(a32, b[4 * ks], b[4 * ks + 1], b[4 * ks + 2], b[4 * ks + 3], desc_nmajor(t16, 8 + ks), 1);
            wg_commit();
        };
        auto block_mma = [&](uint32_t sb, uint32_t ph, bool pass_turn) {
            mbar_wait(full + 8 * sb, ph);
            bar_sync(my_bar);
            half_mma(q, ob, ring16 + sb * T16, zero);
            mbar_wait(full + 8 * sb + 8, ph);
            half_mma(ob + 32, p, ring16 + (sb + 1) * T16, 1);
            if (pass_turn) bar_arrive(other_bar);
        };
        auto send_strips = [&](int u) {
            const uint32_t t = opaque(t128);
            const int d0 = (grp & 4) ^ (4 * u);
            uint4* dst = sc->part + (((qt * 8 + d0) * 9 + u) * 2 + wg) * 512 + (grp & 3) * 128 + t;
#pragma unroll
            for (int i = 0; i < 4; i++) send(dst + i * 9 * 1024, a32 + 8 * i);
            if ((t & 31) < 4) hint(d0 + (t & 31), u * 8 + (grp & 3) * 2 + wg);
        };
        uint32_t xs[4], gs[4];
        {
            [[maybe_unused]] const int c = 9;
            TS(0);
            auto fetch_o = [&](int lo, int hi) {
#pragma unroll
                for (int i = lo; i < hi; i++)
                    lds128(qsrc + (1 + (i >> 3)) * TILE_BYTES + (i & 7) * 512, ob[4 * i], ob[4 * i + 1], ob[4 * i + 2], ob[4 * i + 3]);
            };
            fetch_o(0, 3);
            bar_sync(my_bar);
            wg_fence();
            mma_tile<1>(o, p, ring16 + 3 * T16, 1);
            sched_fence(zero);
            inv_sums(il0, il1);
            asm volatile("" : "+f"(il0), "+f"(il1));
            sched_fence(zero);
            fetch_o(3, 6);
            wg_fence();
#pragma unroll
            for (int ks = 0; ks < 8; ks++) {
                wgmma_rs64(a32, q[4 * ks], q[4 * ks + 1], q[4 * ks + 2], q[4 * ks + 3], desc_nmajor(ring16, ks), ks);
                if (ks == 3) { wg_commit(); sched_fence(zero); fetch_o(6, 8); wg_fence(); }
            }
            TS(1);
#pragma unroll
            for (int ks = 0; ks < 8; ks++) wgmma_rs64(a32, ob[4 * ks], ob[4 * ks + 1], ob[4 * ks + 2], ob[4 * ks + 3], desc_nmajor(ring16, 8 + ks), 1);
            wg_commit();
            TS(2);
            bar_arrive(other_bar);
            wg_wait<1>();
            release_at<24>(rel);
            pin(o);
#pragma unroll
            for (int i = 0; i < 32; i++) {
                const float r = (i & 1) ? il1 : il0;
                asm volatile("cvt.rn.bf16x2.f32 %0, %1, %2;" : "=r"(p[i]) : "f"(o[2 * i + 1] * r), "f"(o[2 * i] * r));
                if ((i & 7) == 7) fetch_o(8 + (i >> 3) * 2, 10 + (i >> 3) * 2);
            }
            TS(3);
            mbar_wait(full + 8, 0);
            wg_wait<0>();
            release_at<0>(rel);
            __syncwarp();
            if (lane == 0) mbar_arrive(vacant);
            TS(4);
            bar_sync(my_bar);
            half_mma(ob + 32, p, ring16 + T16, 1);
            TS(5);
            bar_arrive(other_bar);
            TRM(66);
            TG(113);
            mbar_wait(routed, 0);
            asm volatile("ld.shared.u32 %0, [%1];" : "=r"(ep) : "r"(epoch));
            tag = ep << 16;
            const uint4* src = sc->gate + (blockIdx.x * 5 + 4) * 512 + threadIdx.x;
            asm volatile("ld.global.cg.v4.u32 {%0, %1, %2, %3}, [%4];" : "=r"(xs[0]), "=r"(xs[1]), "=r"(xs[2]), "=r"(xs[3]) : "l"(src));
            asm volatile("ld.global.cg.v4.u32 {%0, %1, %2, %3}, [%4];" : "=r"(gs[0]), "=r"(gs[1]), "=r"(gs[2]), "=r"(gs[3]) : "l"(src + 256));
            sched_fence(zero);
            wg_wait<0>();
            TS(6);
            release_at<8>(rel);
            pin(a32);
            send_strips(0);
            TS(7);
        }
        uint32_t v[4][4];
        auto stale = [&]() {
            return __any_sync(0xffffffffu, lop3<0xA8>(lop3<0x7E>(v[0][0], v[1][0], tag), lop3<0x7E>(v[2][0], v[3][0], tag), 0x10000u));
        };
        auto recv = [&](int u) {
            mbar_wait(rfull + 16 * u + 8 * wg, 0);
#pragma unroll
            for (int i = 0; i < 4; i++)
                lds128(stash + (u >= 6 ? u - 6 : u) * 16384 + wg * 8192 + i * 2048 + t128 * 16, v[i][0], v[i][1], v[i][2], v[i][3]);
            if (stale()) {
                const uint4* src = sc->part + (((qt * 8 + grp) * 9 + u) * 2 + wg) * 512 + opaque(t128);
                do {
#pragma unroll
                    for (int i = 0; i < 4; i++)
                        asm volatile("ld.relaxed.gpu.global.v4.u32 {%0, %1, %2, %3}, [%4];" : "=r"(v[i][0]), "=r"(v[i][1]), "=r"(v[i][2]), "=r"(v[i][3])
                                     : "l"(src + i * 128) : "memory");
                } while (stale());
            }
            if (u < 3 && lane == 0) mbar_arrive(rdone + (u * 2 + wg) * 8);
        };
        auto accumulate = [&](float* dst, int stride) {
#pragma unroll
            for (int i = 0; i < 4; i++) {
                float* a = dst + stride * i;
                a[0] += bf_lo(v[i][0]);
                a[1] += __uint_as_float(lop3<0xEC>(v[i][0], half, 0xfffe0000u));
#pragma unroll
                for (int k = 1; k < 4; k++) { a[2 * k] += bf_lo(v[i][k]); a[2 * k + 1] += bf_hi(v[i][k]); }
            }
        };
        auto gate = [](uint32_t x2, uint32_t g2, float lo, float hi) {
            uint32_t sv = pack_bf16(lo, hi);
            asm("mul.rn.bf16x2 %0, %0, %1;" : "+r"(sv) : "r"(g2));
            asm("add.rn.bf16x2 %0, %0, %1;" : "+r"(sv) : "r"(x2));
            return sv;
        };
        uint4* const outbox = sc->part + qt * (8 * 9 * 1024) + wg * 512 + t128;
        auto step_o = [&](int f) {
            [[maybe_unused]] const int c = f;
            const uint32_t sb = (f & 1) ? 0 : 2;
            block_mma(sb, (((f + 3) >> 1) ^ f) & 1, true);
            wg_wait<1>();
            const uint32_t rl = rel && f < 7 ? rel + 8 * sb : 0;
            release_at<0>(rl);
            if (f >= 1) recv(f - 1);
            wg_wait<0>();
            TS(0);
            release_at<8>(rl);
            pin(a32);
            if (f == 0) {
                send_strips(1);
            } else {
                const int d = (grp + f) & 7;
#pragma unroll
                for (int i = 0; i < 4; i++) send(outbox + (d * 9 + f + 1) * 1024 + i * 128, a32 + 8 * i);
                if (lane == 0) hint(d, 14 + 2 * f + wg);
            }
            TS(1);
        };
        {
            float st[8] = {};
#pragma unroll 1
            for (int f = 0; f < 3; f++) {
                [[maybe_unused]] const int c = f;
                step_o(f);
                if (f >= 1) accumulate(st, 0);
                TS(2);
            }
            uint32_t w[4];
#pragma unroll
            for (int i = 0; i < 4; i++) w[i] = gate(xs[i], gs[i], st[2 * i], st[2 * i + 1]);
            const bool odd = lane & 1;
            const uint32_t r0 = __shfl_xor_sync(0xffffffffu, odd ? w[0] : w[2], 1), r1 = __shfl_xor_sync(0xffffffffu, odd ? w[1] : w[3], 1);
            uint2* dst = (uint2*)out + (qt * 128 + warp * 16 + (lane >> 2)) * (DM / 4) + 128 + grp * 4 + (lane & 1) * 2 + ((lane >> 1) & 1);
            dst[0] = odd ? make_uint2(r0, w[2]) : make_uint2(w[0], r0);
            dst[2 * DM] = odd ? make_uint2(r1, w[3]) : make_uint2(w[1], r1);
        }
#pragma unroll
        for (int i = 0; i < 32; i++) own[i] = 0.f;
#pragma unroll 1
        for (int f = 3; f < 8; f++) {
            [[maybe_unused]] const int c = f;
            step_o(f);
            accumulate(own, 8);
            TS(2);
        }
        {
            [[maybe_unused]] const int c = 8;
            recv(7);
            accumulate(own, 8);
            TS(7);
            block_mma(2, 1, wg == 0);
            TRM(71);
            TS(0);
            recv(8);
            accumulate(own, 8);
            TS(1);
            wg_wait<1>();
            uint32_t xv[16], gv[16];
            mbar_wait(xgfull, 0);
            if (lane == 0) mbar_arrive(alldone);
#pragma unroll
            for (int j = 0; j < 4; j++) {
                lds128(stash + 3 * 16384 + j * 8192 + threadIdx.x * 16, xv[4 * j], xv[4 * j + 1], xv[4 * j + 2], xv[4 * j + 3]);
                lds128(stash + 3 * 16384 + j * 8192 + 4096 + threadIdx.x * 16, gv[4 * j], gv[4 * j + 1], gv[4 * j + 2], gv[4 * j + 3]);
            }
            TS(2);
            wg_wait<0>();
            pin(a32);
#pragma unroll
            for (int i = 0; i < 32; i++) own[i] += a32[i];
            TS(3);
            const uint32_t tb = ring + warp * 2048;
#pragma unroll
            for (int j = 0; j < 4; j++)
                stsm4(tb + (lane & 15) * 128 + (((2 * j + (lane >> 4)) ^ (lane & 7)) << 4),
                      gate(xv[4 * j], gv[4 * j], own[8 * j], own[8 * j + 1]), gate(xv[4 * j + 1], gv[4 * j + 1], own[8 * j + 2], own[8 * j + 3]),
                      gate(xv[4 * j + 2], gv[4 * j + 2], own[8 * j + 4], own[8 * j + 5]), gate(xv[4 * j + 3], gv[4 * j + 3], own[8 * j + 6], own[8 * j + 7]));
            __syncwarp();
#pragma unroll
            for (int j = 0; j < 4; j++) {
                const uint32_t row = j * 4 + (lane >> 3);
                uint4 v;
                lds128(tb + row * 128 + (((lane & 7) ^ (row & 7)) << 4), v.x, v.y, v.z, v.w);
                ((uint4*)out)[(qt * 128 + warp * 16 + row) * (DM / 8) + grp * 8 + (lane & 7)] = v;
            }
        }
        TRM(73);
        TG(111);
    }
}

typedef CUresult (*EncodeFn)(CUtensorMap*, CUtensorMapDataType, cuuint32_t, void*, const cuuint64_t*, const cuuint64_t*,
                             const cuuint32_t*, const cuuint32_t*, CUtensorMapInterleave, CUtensorMapSwizzle,
                             CUtensorMapL2promotion, CUtensorMapFloatOOBfill);

void make_map(EncodeFn enc, CUtensorMap* tm, const void* ptr, uint64_t cols, uint64_t rows) {
    cuuint64_t gd[2] = {cols, rows};
    cuuint64_t gs[1] = {cols * 2};
    cuuint32_t bd[2] = {64, 128};
    cuuint32_t es[2] = {1, 1};
    enc(tm, CU_TENSOR_MAP_DATA_TYPE_BFLOAT16, 2, const_cast<void*>(ptr), gd, gs, bd, es, CU_TENSOR_MAP_INTERLEAVE_NONE,
        CU_TENSOR_MAP_SWIZZLE_128B, CU_TENSOR_MAP_L2_PROMOTION_L2_256B, CU_TENSOR_MAP_FLOAT_OOB_FILL_NONE);
}

}

extern "C" void kernel_launch(void* const* d_in, const int* in_sizes, int n_in, void* d_out, int out_size) {
    const __nv_bfloat16* x = (const __nv_bfloat16*)d_in[0];
    const __nv_bfloat16* wr = (const __nv_bfloat16*)d_in[6];
    __nv_bfloat16* out = (__nv_bfloat16*)d_out;

    EncodeFn enc = nullptr;
    cudaDriverEntryPointQueryResult qr;
    cudaGetDriverEntryPoint("cuTensorMapEncodeTiled", (void**)&enc, cudaEnableDefault, &qr);
    CUtensorMap tm_x, tm_wq, tm_k, tm_v, tm_wo, tm_g, tm_u, tm_d;
    {
        cuuint64_t gd[3] = {64, SEQ, DM / 64};
        cuuint64_t gs[2] = {DM * 2, 128};
        cuuint32_t bd[3] = {64, 64, 2};
        cuuint32_t es[3] = {1, 1, 1};
        enc(&tm_x, CU_TENSOR_MAP_DATA_TYPE_BFLOAT16, 3, d_in[0], gd, gs, bd, es, CU_TENSOR_MAP_INTERLEAVE_NONE,
            CU_TENSOR_MAP_SWIZZLE_128B, CU_TENSOR_MAP_L2_PROMOTION_L2_256B, CU_TENSOR_MAP_FLOAT_OOB_FILL_NONE);
    }
    make_map(enc, &tm_k, d_in[1], DH, (uint64_t)NH * SEQ);
    make_map(enc, &tm_v, d_in[2], DH, (uint64_t)NH * SEQ);
    make_map(enc, &tm_wq, d_in[3], NH * DH, DM);
    make_map(enc, &tm_wo, d_in[4], DM, NH * DH);
    make_map(enc, &tm_g, d_in[7], FF, DM);
    make_map(enc, &tm_u, d_in[8], FF, DM);
    make_map(enc, &tm_d, d_in[9], DM, FF);
    cudaFuncSetAttribute(fused_attn_kernel, cudaFuncAttributeMaxDynamicSharedMemorySize, SMEM_BYTES);

    Scratch* sc = nullptr;
    cudaGetSymbolAddress((void**)&sc, g_scratch);

    cudaLaunchConfig_t cfg = {};
    cfg.gridDim = dim3(N_MAIN + N_MOE);
    cfg.blockDim = dim3(384);
    cfg.dynamicSmemBytes = SMEM_BYTES;
    cfg.stream = cudaStreamPerThread;
    cudaLaunchAttribute at[1];
    at[0].id = cudaLaunchAttributeClusterDimension;
    at[0].val.clusterDim.x = 2; at[0].val.clusterDim.y = 1; at[0].val.clusterDim.z = 1;
    cfg.attrs = at; cfg.numAttrs = 1;
    cudaLaunchKernelEx(&cfg, fused_attn_kernel, x, wr, out, sc, tm_x, tm_wq, tm_k, tm_v, tm_wo, tm_g, tm_u, tm_d);
}
```

```cpp
#include <cuda_runtime.h>
#include <cuda.h>
#include <cuda_bf16.h>
#include <stdint.h>

namespace {

constexpr int SEQ = 2048, DM = 640, NH = 32, DH = 128, FF = 1728, CAP = 8;
constexpr int NSLOT = 4;
constexpr int TILE_BYTES = 32768;
constexpr uint32_t RING_OFFSET = 1024;
constexpr int SMEM_BYTES = (NSLOT + 3) * TILE_BYTES + 416 + 1408 + 96;
constexpr int N_MAIN = 128, N_MOE = 4;

struct Scratch {
    uint4 part[16 * 8 * 9 * 2 * 4 * 128];
    uint4 gate[N_MAIN * 5 * 2 * 256];
    uint4 flag[16 * 8 * 32];
    uint4 qoff[16 * 4 * 2048];
    uint32_t flag_q[16];
    uint4 rare[N_MAIN * 17 * 256];
    float y[N_MOE * CAP * DM];
    uint2 routed[CAP * DM / 4];
    uint2 stat[SEQ];
    float r[SEQ];
    int idx[CAP];
    uint32_t flag_r[N_MOE], flag_y[N_MOE], flag_u[N_MOE];
    uint32_t epoch[N_MAIN + N_MOE];
};
__device__ Scratch g_scratch;

__device__ __forceinline__ uint32_t smem_u32(const void* p) { return (uint32_t)__cvta_generic_to_shared(p); }
__device__ __forceinline__ void mbar_init(uint32_t bar, uint32_t cnt) {
    asm volatile("mbarrier.init.shared::cta.b64 [%0], %1;" ::"r"(bar), "r"(cnt) : "memory");
}
#define HOTW 2
__device__ __forceinline__ void mbar_wait(uint32_t bar, uint32_t parity) {
    asm volatile(
        "{\n.reg .pred p;\n"
        "LOOP:\n"
        "mbarrier.try_wait.parity.shared::cta.b64 p, [%0], %1;\n"
        "@!p bra.uni LOOP;\n"
        "DONE:\n}\n" ::"r"(bar), "r"(parity) : "memory");
}
__device__ __forceinline__ void mbar_wait_hot(uint32_t bar, uint32_t parity) {
    asm volatile(
        "{\n.reg .pred p;\n.reg .u32 c;\n"
        "mbarrier.test_wait.parity.shared::cta.b64 p, [%0], %1;\n"
        "@p bra.uni DONE;\n"
        "mov.u32 c, 0;\n"
        "LOOP:\n"
        "mbarrier.try_wait.parity.shared::cta.b64 p, [%0], %1;\n"
        "@p bra.uni DONE;\n"
        "add.u32 c, c, 1;\n"
        "setp.lt.u32 p, c, 2000000;\n"
        "@p bra.uni LOOP;\n"
        "trap;\n"
        "DONE:\n}\n" ::"r"(bar), "r"(parity) : "memory");
}
__device__ __forceinline__ void mbar_wait_bounded(uint32_t bar, uint32_t parity) {
    asm volatile(
        "{\n.reg .pred p;\n.reg .u32 c;\n"
        "mov.u32 c, 0;\n"
        "LOOP:\n"
        "mbarrier.try_wait.parity.shared::cta.b64 p, [%0], %1;\n"
        "@p bra.uni DONE;\n"
        "add.u32 c, c, 1;\n"
        "setp.lt.u32 p, c, 2000000;\n"
        "@p bra.uni LOOP;\n"
        "trap;\n"
        "DONE:\n}\n" ::"r"(bar), "r"(parity) : "memory");
}
__device__ __forceinline__ void mbar_wait_sleep(uint32_t bar, uint32_t parity) {
    asm volatile(
        "{\n.reg .pred p;\n.reg .u32 c;\n"
        "mov.u32 c, 0;\n"
        "LOOP:\n"
        "mbarrier.test_wait.parity.shared::cta.b64 p, [%0], %1;\n"
        "@p bra.uni DONE;\n"
        "nanosleep.u32 500;\n"
        "add.u32 c, c, 1;\n"
        "setp.lt.u32 p, c, 1000000;\n"
        "@p bra.uni LOOP;\n"
        "trap;\n"
        "DONE:\n}\n" ::"r"(bar), "r"(parity) : "memory");
}
__device__ __forceinline__ void mbar_expect_tx(uint32_t bar, uint32_t bytes) {
    asm volatile("mbarrier.arrive.expect_tx.shared::cta.b64 _, [%0], %1;" ::"r"(bar), "r"(bytes) : "memory");
}
template <int OFF>
__device__ __forceinline__ void release_at(uint32_t bar) {
    asm volatile(
        "{\n.reg .pred p;\n"
        "setp.ne.u32 p, %0, 0;\n"
        "@p mbarrier.arrive.shared::cluster.b64 _, [%0 + %1];\n}\n" ::"r"(bar), "n"(OFF) : "memory");
}
__device__ __forceinline__ void sched_fence(int zero) {
    asm volatile("{\n.reg .pred p;\n.reg .u32 c;\nsetp.ne.s32 p, %0, 0;\n@p mov.u32 c, %%clock;\n@p st.shared.u32 [%0], c;\n}\n" ::"r"(zero) : "memory");
}
__device__ __forceinline__ bool elect_one() {
    uint32_t r;
    asm volatile("{\n.reg .pred p;\nelect.sync _|p, 0xffffffff;\nselp.u32 %0, 1, 0, p;\n}\n" : "=r"(r));
    return r;
}
__device__ __forceinline__ uint32_t opaque(uint32_t v) {
    uint32_t r;
    asm volatile("mov.u32 %0, %1;" : "=r"(r) : "r"(v));
    return r;
}
__device__ __forceinline__ void tma_2d(uint32_t dst, const CUtensorMap* tm, uint32_t bar, int c0, int c1) {
    asm volatile(
        "cp.async.bulk.tensor.2d.shared::cluster.global.mbarrier::complete_tx::bytes [%0], [%1, {%3, %4}], [%2];"
        ::"r"(dst), "l"(tm), "r"(bar), "r"(c0), "r"(c1) : "memory");
}
__device__ __forceinline__ void tma_3d(uint32_t dst, const CUtensorMap* tm, uint32_t bar, int c0, int c1, int c2) {
    asm volatile(
        "cp.async.bulk.tensor.3d.shared::cluster.global.mbarrier::complete_tx::bytes [%0], [%1, {%3, %4, %5}], [%2];"
        ::"r"(dst), "l"(tm), "r"(bar), "r"(c0), "r"(c1), "r"(c2) : "memory");
}
__device__ __forceinline__ void tma_2d_mc(uint32_t dst, const CUtensorMap* tm, uint32_t bar, int c0, int c1) {
    asm volatile(
        "cp.async.bulk.tensor.2d.shared::cluster.global.mbarrier::complete_tx::bytes.multicast::cluster "
        "[%0], [%1, {%3, %4}], [%2], %5;"
        ::"r"(dst), "l"(tm), "r"(bar), "r"(c0), "r"(c1), "h"((uint16_t)3) : "memory");
}
__device__ __forceinline__ void tma_prefetch(const CUtensorMap* tm, int c0, int c1) {
    asm volatile("cp.async.bulk.prefetch.tensor.2d.L2.global [%0, {%1, %2}];" ::"l"(tm), "r"(c0), "r"(c1) : "memory");
}
__device__ __forceinline__ void mbar_arrive(uint32_t bar) {
    asm volatile("mbarrier.arrive.shared::cta.b64 _, [%0];" ::"r"(bar) : "memory");
}
__device__ __forceinline__ void flag_set(uint32_t* f, uint32_t v) {
    asm volatile("st.release.gpu.global.u32 [%0], %1;" ::"l"(f), "r"(v) : "memory");
}
template <int SLEEP_NS = 0>
__device__ __forceinline__ void flag_wait(const uint32_t* f, uint32_t v) {
    asm volatile(
        "{\n.reg .pred p;\n.reg .u32 c;\n"
        "LOOP:\n"
        "setp.ne.u32 p, %2, 0;\n"
        "@p nanosleep.u32 %2;\n"
        "ld.acquire.gpu.global.u32 c, [%0];\n"
        "setp.ne.u32 p, c, %1;\n"
        "@p bra LOOP;\n}\n" ::"l"(f), "r"(v), "n"(SLEEP_NS) : "memory");
}
template <int SLEEP_NS>
__device__ __forceinline__ void flag_wait_bounded(const uint32_t* f, uint32_t v) {
    asm volatile(
        "{\n.reg .pred p;\n.reg .u32 c, n;\n"
        "mov.u32 n, 0;\n"
        "LOOP:\n"
        "setp.ne.u32 p, %2, 0;\n"
        "@p nanosleep.u32 %2;\n"
        "ld.acquire.gpu.global.u32 c, [%0];\n"
        "setp.eq.u32 p, c, %1;\n"
        "@p bra DONE;\n"
        "add.u32 n, n, 1;\n"
        "setp.lt.u32 p, n, %3;\n"
        "@p bra LOOP;\n"
        "trap;\n"
        "DONE:\n}\n" ::"l"(f), "r"(v), "n"(SLEEP_NS), "n"(2000000) : "memory");
}
__device__ __forceinline__ void hmma(float (&d)[4], uint32_t a0, uint32_t a1, uint32_t a2, uint32_t a3, uint32_t b0, uint32_t b1) {
    asm volatile("mma.sync.aligned.m16n8k16.row.col.f32.bf16.bf16.f32 {%0,%1,%2,%3}, {%4,%5,%6,%7}, {%8,%9}, {%0,%1,%2,%3};"
                 : "+f"(d[0]), "+f"(d[1]), "+f"(d[2]), "+f"(d[3]) : "r"(a0), "r"(a1), "r"(a2), "r"(a3), "r"(b0), "r"(b1));
}
__device__ __forceinline__ void hmma8(float (&d)[4], uint32_t a0, uint32_t a1, uint32_t b0) {
    asm volatile("mma.sync.aligned.m16n8k8.row.col.f32.bf16.bf16.f32 {%0,%1,%2,%3}, {%4,%5}, {%6}, {%0,%1,%2,%3};"
                 : "+f"(d[0]), "+f"(d[1]), "+f"(d[2]), "+f"(d[3]) : "r"(a0), "r"(a1), "r"(b0));
}
__device__ __forceinline__ void ldsm4(uint32_t addr, uint32_t& a, uint32_t& b, uint32_t& c, uint32_t& d) {
    asm volatile("ldmatrix.sync.aligned.m8n8.x4.shared.b16 {%0, %1, %2, %3}, [%4];"
                 : "=r"(a), "=r"(b), "=r"(c), "=r"(d) : "r"(addr) : "memory");
}
__device__ __forceinline__ void stsm4(uint32_t addr, uint32_t a, uint32_t b, uint32_t c, uint32_t d) {
    asm volatile("stmatrix.sync.aligned.m8n8.x4.shared.b16 [%4], {%0, %1, %2, %3};"
                 ::"r"(a), "r"(b), "r"(c), "r"(d), "r"(addr) : "memory");
}
__device__ __forceinline__ uint32_t bf2_sub(uint32_t a, uint32_t b) {
    uint32_t d;
    asm("sub.rn.bf16x2 %0, %1, %2;" : "=r"(d) : "r"(a), "r"(b));
    return d;
}
template <int LUT>
__device__ __forceinline__ uint32_t lop3(uint32_t a, uint32_t b, uint32_t c) {
    uint32_t d;
    asm("lop3.b32 %0, %1, %2, %3, %4;" : "=r"(d) : "r"(a), "r"(b), "r"(c), "n"(LUT));
    return d;
}
__device__ __forceinline__ float rcp(float x) {
    float y;
    asm("rcp.approx.ftz.f32 %0, %1;" : "=f"(y) : "f"(x));
    return y;
}
__device__ __forceinline__ void bar_sync(int id) { asm volatile("bar.sync %0, 256;" ::"r"(id) : "memory"); }
__device__ __forceinline__ void bar_arrive(int id) { asm volatile("bar.arrive %0, 256;" ::"r"(id) : "memory"); }
__device__ __forceinline__ void wg_fence() { asm volatile("wgmma.fence.sync.aligned;" ::: "memory"); }
__device__ __forceinline__ void wg_commit() { asm volatile("wgmma.commit_group.sync.aligned;" ::: "memory"); }
template <int N> __device__ __forceinline__ void wg_wait() { asm volatile("wgmma.wait_group.sync.aligned %0;" ::"n"(N) : "memory"); }
template <int N>
__device__ __forceinline__ void pin(float (&d)[N]) {
#pragma unroll
    for (int i = 0; i < N; i++) asm volatile("" : "+f"(d[i])::"memory");
}
__device__ __forceinline__ uint32_t pack_bf16(float lo, float hi) {
    uint32_t r;
    asm("cvt.rn.bf16x2.f32 %0, %1, %2;" : "=r"(r) : "f"(hi), "f"(lo));
    return r;
}
__device__ __forceinline__ float bf_lo(uint32_t v) { return __uint_as_float(v << 16); }
__device__ __forceinline__ float bf_hi(uint32_t v) { return __uint_as_float(v & 0xffff0000u); }
__device__ __forceinline__ float bf_round(float v) { return __bfloat162float(__float2bfloat16_rn(v)); }
__device__ __forceinline__ float ex2(float x) {
    float y;
    asm("ex2.approx.ftz.f32 %0, %1;" : "=f"(y) : "f"(x));
    return y;
}
__device__ __forceinline__ void sts128(uint32_t addr, uint32_t a, uint32_t b, uint32_t c, uint32_t d) {
    asm volatile("st.shared.v4.b32 [%0], {%1, %2, %3, %4};" ::"r"(addr), "r"(a), "r"(b), "r"(c), "r"(d) : "memory");
}
__device__ __forceinline__ void lds128(uint32_t addr, uint32_t& a, uint32_t& b, uint32_t& c, uint32_t& d) {
    asm volatile("ld.shared.v4.b32 {%0, %1, %2, %3}, [%4];" : "=r"(a), "=r"(b), "=r"(c), "=r"(d) : "r"(addr) : "memory");
}

template <int OFF>
__device__ __forceinline__ void lds128_if(bool on, uint32_t addr, uint32_t& a, uint32_t& b, uint32_t& c, uint32_t& d) {
    asm volatile("{\n.reg .pred p;\nsetp.ne.u32 p, %5, 0;\n@p ld.shared.v4.b32 {%0, %1, %2, %3}, [%4 + %6];\n}\n"
                 : "+r"(a), "+r"(b), "+r"(c), "+r"(d) : "r"(addr), "r"((uint32_t)on), "n"(OFF) : "memory");
}

template <int TB>
__device__ __forceinline__ void wgmma_rs(float (&d)[64], uint32_t a0, uint32_t a1, uint32_t a2, uint32_t a3,
                                         uint64_t desc, int scale_d) {
    asm volatile(
        "{\n.reg .pred p;\nsetp.ne.b32 p, %69, 0;\n"
        "wgmma.mma_async.sync.aligned.m64n128k16.f32.bf16.bf16 "
        "{%0,%1,%2,%3,%4,%5,%6,%7,%8,%9,%10,%11,%12,%13,%14,%15,%16,%17,%18,%19,%20,%21,%22,%23,%24,%25,%26,%27,%28,%29,%30,%31,"
        "%32,%33,%34,%35,%36,%37,%38,%39,%40,%41,%42,%43,%44,%45,%46,%47,%48,%49,%50,%51,%52,%53,%54,%55,%56,%57,%58,%59,%60,%61,%62,%63},"
        "{%64,%65,%66,%67}, %68, p, 1, 1, %70;\n}\n"
        : "+f"(d[0]), "+f"(d[1]), "+f"(d[2]), "+f"(d[3]), "+f"(d[4]), "+f"(d[5]), "+f"(d[6]), "+f"(d[7]),
          "+f"(d[8]), "+f"(d[9]), "+f"(d[10]), "+f"(d[11]), "+f"(d[12]), "+f"(d[13]), "+f"(d[14]), "+f"(d[15]),
          "+f"(d[16]), "+f"(d[17]), "+f"(d[18]), "+f"(d[19]), "+f"(d[20]), "+f"(d[21]), "+f"(d[22]), "+f"(d[23]),
          "+f"(d[24]), "+f"(d[25]), "+f"(d[26]), "+f"(d[27]), "+f"(d[28]), "+f"(d[29]), "+f"(d[30]), "+f"(d[31]),
          "+f"(d[32]), "+f"(d[33]), "+f"(d[34]), "+f"(d[35]), "+f"(d[36]), "+f"(d[37]), "+f"(d[38]), "+f"(d[39]),
          "+f"(d[40]), "+f"(d[41]), "+f"(d[42]), "+f"(d[43]), "+f"(d[44]), "+f"(d[45]), "+f"(d[46]), "+f"(d[47]),
          "+f"(d[48]), "+f"(d[49]), "+f"(d[50]), "+f"(d[51]), "+f"(d[52]), "+f"(d[53]), "+f"(d[54]), "+f"(d[55]),
          "+f"(d[56]), "+f"(d[57]), "+f"(d[58]), "+f"(d[59]), "+f"(d[60]), "+f"(d[61]), "+f"(d[62]), "+f"(d[63])
        : "r"(a0), "r"(a1), "r"(a2), "r"(a3), "l"(desc), "r"(scale_d), "n"(TB));
}
__device__ __forceinline__ void wgmma_ss(float (&d)[64], uint64_t desc_a, uint64_t desc_b, int scale_d) {
    asm volatile(
        "{\n.reg .pred p;\nsetp.ne.b32 p, %66, 0;\n"
        "wgmma.mma_async.sync.aligned.m64n128k16.f32.bf16.bf16 "
        "{%0,%1,%2,%3,%4,%5,%6,%7,%8,%9,%10,%11,%12,%13,%14,%15,%16,%17,%18,%19,%20,%21,%22,%23,%24,%25,%26,%27,%28,%29,%30,%31,"
        "%32,%33,%34,%35,%36,%37,%38,%39,%40,%41,%42,%43,%44,%45,%46,%47,%48,%49,%50,%51,%52,%53,%54,%55,%56,%57,%58,%59,%60,%61,%62,%63},"
        "%64, %65, p, 1, 1, 0, 1;\n}\n"
        : "+f"(d[0]), "+f"(d[1]), "+f"(d[2]), "+f"(d[3]), "+f"(d[4]), "+f"(d[5]), "+f"(d[6]), "+f"(d[7]),
          "+f"(d[8]), "+f"(d[9]), "+f"(d[10]), "+f"(d[11]), "+f"(d[12]), "+f"(d[13]), "+f"(d[14]), "+f"(d[15]),
          "+f"(d[16]), "+f"(d[17]), "+f"(d[18]), "+f"(d[19]), "+f"(d[20]), "+f"(d[21]), "+f"(d[22]), "+f"(d[23]),
          "+f"(d[24]), "+f"(d[25]), "+f"(d[26]), "+f"(d[27]), "+f"(d[28]), "+f"(d[29]), "+f"(d[30]), "+f"(d[31]),
          "+f"(d[32]), "+f"(d[33]), "+f"(d[34]), "+f"(d[35]), "+f"(d[36]), "+f"(d[37]), "+f"(d[38]), "+f"(d[39]),
          "+f"(d[40]), "+f"(d[41]), "+f"(d[42]), "+f"(d[43]), "+f"(d[44]), "+f"(d[45]), "+f"(d[46]), "+f"(d[47]),
          "+f"(d[48]), "+f"(d[49]), "+f"(d[50]), "+f"(d[51]), "+f"(d[52]), "+f"(d[53]), "+f"(d[54]), "+f"(d[55]),
          "+f"(d[56]), "+f"(d[57]), "+f"(d[58]), "+f"(d[59]), "+f"(d[60]), "+f"(d[61]), "+f"(d[62]), "+f"(d[63])
        : "l"(desc_a), "l"(desc_b), "r"(scale_d));
}
__device__ __forceinline__ void wgmma_rs64(float (&d)[32], uint32_t a0, uint32_t a1, uint32_t a2, uint32_t a3,
                                           uint64_t desc, int scale_d) {
    asm volatile(
        "{\n.reg .pred p;\nsetp.ne.b32 p, %37, 0;\n"
        "wgmma.mma_async.sync.aligned.m64n64k16.f32.bf16.bf16 "
        "{%0,%1,%2,%3,%4,%5,%6,%7,%8,%9,%10,%11,%12,%13,%14,%15,%16,%17,%18,%19,%20,%21,%22,%23,%24,%25,%26,%27,%28,%29,%30,%31},"
        "{%32,%33,%34,%35}, %36, p, 1, 1, 1;\n}\n"
        : "+f"(d[0]), "+f"(d[1]), "+f"(d[2]), "+f"(d[3]), "+f"(d[4]), "+f"(d[5]), "+f"(d[6]), "+f"(d[7]),
          "+f"(d[8]), "+f"(d[9]), "+f"(d[10]), "+f"(d[11]), "+f"(d[12]), "+f"(d[13]), "+f"(d[14]), "+f"(d[15]),
          "+f"(d[16]), "+f"(d[17]), "+f"(d[18]), "+f"(d[19]), "+f"(d[20]), "+f"(d[21]), "+f"(d[22]), "+f"(d[23]),
          "+f"(d[24]), "+f"(d[25]), "+f"(d[26]), "+f"(d[27]), "+f"(d[28]), "+f"(d[29]), "+f"(d[30]), "+f"(d[31])
        : "r"(a0), "r"(a1), "r"(a2), "r"(a3), "l"(desc), "r"(scale_d));
}
__device__ __forceinline__ void wgmma_ss64(float (&d)[32], uint64_t desc_a, uint64_t desc_b, int scale_d) {
    asm volatile(
        "{\n.reg .pred p;\nsetp.ne.b32 p, %34, 0;\n"
        "wgmma.mma_async.sync.aligned.m64n64k16.f32.bf16.bf16 "
        "{%0,%1,%2,%3,%4,%5,%6,%7,%8,%9,%10,%11,%12,%13,%14,%15,%16,%17,%18,%19,%20,%21,%22,%23,%24,%25,%26,%27,%28,%29,%30,%31},"
        "%32, %33, p, 1, 1, 0, 1;\n}\n"
        : "+f"(d[0]), "+f"(d[1]), "+f"(d[2]), "+f"(d[3]), "+f"(d[4]), "+f"(d[5]), "+f"(d[6]), "+f"(d[7]),
          "+f"(d[8]), "+f"(d[9]), "+f"(d[10]), "+f"(d[11]), "+f"(d[12]), "+f"(d[13]), "+f"(d[14]), "+f"(d[15]),
          "+f"(d[16]), "+f"(d[17]), "+f"(d[18]), "+f"(d[19]), "+f"(d[20]), "+f"(d[21]), "+f"(d[22]), "+f"(d[23]),
          "+f"(d[24]), "+f"(d[25]), "+f"(d[26]), "+f"(d[27]), "+f"(d[28]), "+f"(d[29]), "+f"(d[30]), "+f"(d[31])
        : "l"(desc_a), "l"(desc_b), "r"(scale_d));
}
__device__ __forceinline__ uint64_t desc_kmajor(uint32_t tile16, int ks) {
    uint32_t lo = tile16 + ((ks >> 2) * 1024 + (ks & 3) * 2 + (1u << 16));
    return ((uint64_t)0x40000040u << 32) | lo;
}
__device__ __forceinline__ uint64_t desc_nmajor(uint32_t tile16, int ks) {
    uint32_t lo = tile16 + (ks * 128 + (1024u << 16));
    return ((uint64_t)0x40000040u << 32) | lo;
}
template <int TB>
__device__ __forceinline__ void mma_tile(float (&d)[64], const uint32_t* a, uint32_t tile16, int accumulate) {
#pragma unroll
    for (int ks = 0; ks < 8; ks++)
        wgmma_rs<TB>(d, a[4 * ks], a[4 * ks + 1], a[4 * ks + 2], a[4 * ks + 3],
                     TB ? desc_nmajor(tile16, ks) : desc_kmajor(tile16, ks), ks == 0 ? accumulate : 1);
    wg_commit();
}

template <int V> struct cint { static constexpr int value = V; };
#define GPF 126
#define XN 2
#define FINK 3
#define G4 0
#define EARLYA 0
#define PUTF 1
#define QB 1
#define INVP 0
#define QAT 110
#define FSPLIT 2
#define SPLIT 32
#define SPLITO 24

#define TRM(i)
#define TR(i)
#define TG(i)
#define PT(k)
#define TS(k)
#define TA(k)
#define TL(k)
#define TF(i)
#define TH(w, i)
#define TC(k)

__device__ __forceinline__ float silu_f(float v) { return v * rcp(1.f + ex2(v * -1.4426950408889634f)); }

__device__ __forceinline__ float inv_den(float var) {
    float r;
    asm("sqrt.approx.f32 %0, %1;" : "=f"(r) : "f"(bf_round(bf_round(var) + 1e-5f)));
    return rcp(bf_round(r));
}
__device__ __forceinline__ uint32_t normalise(uint32_t x2, uint32_t mm, float id) {
    const uint32_t d = bf2_sub(x2, mm);
    return pack_bf16(bf_lo(d) * id, bf_hi(d) * id);
}

__device__ __forceinline__ uint32_t silu2(uint32_t u) { return pack_bf16(silu_f(bf_lo(u)), silu_f(bf_hi(u))); }

__device__ __forceinline__ uint32_t silu2_ln(uint32_t u) {
    const float a = bf_lo(u), b = bf_hi(u);
    const float da = 1.f + ex2(a * -1.4426950408889634f), db = 1.f + ex2(b * -1.4426950408889634f);
    const float r = rcp(da * db);
    return pack_bf16(a * db * r, b * da * r);
}

__device__ __forceinline__ uint2 load_stat(Scratch* sc, int row) {
    uint2 v;
    asm volatile("ld.relaxed.gpu.global.v2.u32 {%0, %1}, [%2];" : "=r"(v.x), "=r"(v.y) : "l"(sc->stat + row) : "memory");
    return make_uint2(__byte_perm(v.x, 0, 0x1010), v.y);
}

constexpr int FSLOT = 6;
__device__ __forceinline__ void ffn_role(Scratch* sc, uint32_t ring, uint32_t ffull, uint32_t fempty, uint32_t alldone, int e, uint32_t ep, int warp,
                                         const __nv_bfloat16* __restrict__ x) {
    const uint32_t xs = ring + FSLOT * TILE_BYTES, hs = xs + 10 * 1024, cand = hs + 8 * 1024, sig = cand + 256;
    int tid;
    asm volatile("mov.u32 %0, %%tid.x;" : "=r"(tid));
    const int lane = tid & 31;
    [[maybe_unused]] const int wg = warp >> 2;
    const int nb = e == N_MOE - 1 ? 6 : 7, nkt = (nb + 1) >> 1;
    auto sync = [] { asm volatile("bar.sync 3, 256;" ::: "memory"); };
    if (tid < N_MOE) flag_wait(sc->flag_r + tid, ep);
    sync();
    TR(6);

    {
        uint32_t key[8];
#pragma unroll
        for (int i = 0; i < 8; i++) {
            const int j = warp * 256 + i * 32 + lane;
            const uint32_t u = __float_as_uint(__ldcg(sc->r + j) + 0.f);
            key[i] = (((u & 0x80000000u) ? ~u : (u | 0x80000000u)) & 0xffff0000u) | (uint32_t)(SEQ - j);
        }
#pragma unroll 1
        for (int k = 0; k < CAP; k++) {
            uint32_t b = key[0];
#pragma unroll
            for (int i = 1; i < 8; i++) b = max(b, key[i]);
            b = __reduce_max_sync(0xffffffffu, b);
#pragma unroll
            for (int i = 0; i < 8; i++) if (key[i] == b) key[i] = 0;
            if (lane == 0) asm volatile("st.shared.u32 [%0], %1;" ::"r"(cand + (warp * 8 + k) * 4), "r"(b) : "memory");
        }
    }
    sync();
    {
        uint32_t k0, k1, b = 0;
        asm volatile("ld.shared.v2.u32 {%0, %1}, [%2];" : "=r"(k0), "=r"(k1) : "r"(cand + lane * 8));
#pragma unroll 1
        for (int k = 0; k <= warp; k++) {
            b = __reduce_max_sync(0xffffffffu, max(k0, k1));
            if (k0 == b) k0 = 0;
            if (k1 == b) k1 = 0;
        }
        const int row = SEQ - (int)(b & 0xffffu);
        const uint2 st = load_stat(sc, row);
        uint4 v[3];
#pragma unroll
        for (int k = 0; k < 3; k++) v[k] = __ldg((const uint4*)(x + (size_t)row * DM) + min(lane + 32 * k, DM / 8 - 1));
#pragma unroll
        for (int k = 0; k < 3; k++) {
            const int i = lane + 32 * k;
            const float id = __uint_as_float(st.y);
            if (i < DM / 8)
                sts128(xs + (i >> 3) * 1024 + warp * 128 + (((i & 7) ^ warp) << 4), normalise(v[k].x, st.x, id), normalise(v[k].y, st.x, id),
                       normalise(v[k].z, st.x, id), normalise(v[k].w, st.x, id));
        }
        asm volatile("fence.proxy.async.shared::cta;" ::: "memory");
        if (lane == 0) {
            const float sg = bf_round(rcp(1.f + __expf(-__ldcg(sc->r + row))));
            asm volatile("st.shared.v2.b32 [%0], {%1, %2};" ::"r"(sig + warp * 8), "f"(sg), "r"(row) : "memory");
        }
    }
    sync();
    TR(7);

    {
        float acc[64];
        const int g = lane >> 2, t4 = lane & 3;
        auto block = [&](uint32_t a, uint32_t n, int step, int halves) {
#pragma unroll 1
            for (int i = 0; i < halves; i += 2, n += step) {
                const uint32_t s = n % FSLOT;
                mbar_wait(ffull + 8 * s, (n / FSLOT) & 1);
                const uint32_t a16 = (((a + i * 1024) & 0x3FFFFu) >> 4) | (1u << 16);
                const uint32_t b16 = ((ring + s * TILE_BYTES) & 0x3FFFFu) >> 4;
                auto mmas = [&](auto n_c) {
                    wg_fence();
#pragma unroll
                    for (int ks = 0; ks < decltype(n_c)::value; ks++)
                        wgmma_ss(acc, ((uint64_t)0x40000000u << 32) | (a16 + (ks >> 2) * 64 + (ks & 3) * 2), desc_nmajor(b16, ks), ks || i);
                    wg_commit();
                    wg_wait<0>();
                };
                if (i + 1 < halves) mmas(cint<8>());
                else mmas(cint<4>());
                if (lane == 0) mbar_arrive(fempty + 8 * s);
            }
            pin(acc);
        };
#pragma unroll 1
        for (int o = warp >> 2; o < nb; o += 2) {
            const bool pair = (o | 1) < nb;
            block(xs, 5 * (o & ~1) + (pair ? o & 1 : 0), pair ? 2 : 1, 10);
#pragma unroll
            for (int j = 0; j < 8; j++) {
                uint32_t h = pack_bf16(silu_f(bf_round(acc[4 * j])), silu_f(bf_round(acc[4 * j + 1])));
                asm("mul.rn.bf16x2 %0, %0, %1;" : "+r"(h) : "r"(pack_bf16(acc[32 + 4 * j], acc[33 + 4 * j])));
                asm volatile("st.shared.u32 [%0], %1;" ::"r"(hs + o * 1024 + g * 128 + ((j ^ g) << 4) + t4 * 4), "r"(h) : "memory");
            }
        }
        asm volatile("fence.proxy.async.shared::cta;" ::: "memory");
        sync();
        TR(8);
#pragma unroll 1
        for (int o = warp >> 2; o < 5; o += 2) {
            block(hs, 5 * nb + (o & ~1) * nkt + (o & 1), o < 4 ? 2 : 1, nb);
            if ((warp & 3) == 0) {
#pragma unroll
                for (int j = 0; j < 16; j++)
                    *(float2*)(sc->y + (e * CAP + g) * DM + o * 128 + j * 8 + t4 * 2) = make_float2(acc[4 * j], acc[4 * j + 1]);
            }
        }
    }
    sync();
    TR(9);
    if (tid == 0) flag_set(sc->flag_y + e, ep);
    if (tid < N_MOE) flag_wait(sc->flag_y + tid, ep);
    sync();
    if (lane == 0) mbar_arrive(alldone);
#pragma unroll 1
    for (int t = tid; t < 320; t += 256) {
        const int i = 2 * e * DM + t * 4;
        float4 y = __ldcg((const float4*)(sc->y + i));
#pragma unroll
        for (int j = 1; j < N_MOE; j++) {
            const float4 z = __ldcg((const float4*)(sc->y + j * CAP * DM + i));
            y.x += z.x; y.y += z.y; y.z += z.z; y.w += z.w;
        }
        float sg;
        int row;
        asm volatile("ld.shared.v2.b32 {%0, %1}, [%2];" : "=f"(sg), "=r"(row) : "r"(sig + (i / DM) * 8));
        const int o4 = (row * DM + i % DM) / 4;
        const uint2 v = __ldg((const uint2*)x + o4), st = load_stat(sc, row);
        uint32_t u0 = normalise(v.x, st.x, __uint_as_float(st.y)), u1 = normalise(v.y, st.x, __uint_as_float(st.y));
        asm("add.rn.bf16x2 %0, %0, %1;" : "+r"(u0) : "r"(pack_bf16(bf_round(y.x) * sg, bf_round(y.y) * sg)));
        asm("add.rn.bf16x2 %0, %0, %1;" : "+r"(u1) : "r"(pack_bf16(bf_round(y.z) * sg, bf_round(y.w) * sg)));
        sc->routed[i / 4] = make_uint2(silu2(u0), silu2(u1));
        if (i % DM == 0) sc->idx[i / DM] = row;
    }
    sync();
    TR(10);
    if (tid == 0) flag_set(sc->flag_u + e, ep);
}

__global__ void __launch_bounds__(384, 1)
fused_attn_kernel(const __nv_bfloat16* __restrict__ x, const __nv_bfloat16* __restrict__ wr,
                  __nv_bfloat16* __restrict__ out, Scratch* sc,
                  const __grid_constant__ CUtensorMap tm_x, const __grid_constant__ CUtensorMap tm_wq,
                  const __grid_constant__ CUtensorMap tm_k, const __grid_constant__ CUtensorMap tm_v,
                  const __grid_constant__ CUtensorMap tm_wo, const __grid_constant__ CUtensorMap tm_g,
                  const __grid_constant__ CUtensorMap tm_u, const __grid_constant__ CUtensorMap tm_d) {
    PT(0);
    extern __shared__ __align__(16) uint8_t smem_raw[];
    const uint32_t ring = smem_u32(smem_raw);
    const uint32_t stash = ring + NSLOT * TILE_BYTES;
    const uint32_t bars = stash + 3 * TILE_BYTES;
    const uint32_t full = bars, empty = bars + 32;
    const uint32_t xfull = bars + 64;
    const uint32_t rfull = bars + 144;
    const uint32_t rdone = bars + 288;
    const uint32_t vacant = bars + 336, routed = bars + 344, xgfull = bars + 352, gated = bars + 360;
    const uint32_t soon = bars + 376, qfull = bars + 384, epv = bars + 392, alldone = bars + 400;
    const uint32_t epoch = bars + 368;
    [[maybe_unused]] const uint32_t trbuf = bars + 416;
    const uint32_t ffull = rfull, fempty = rfull + 8 * FSLOT, qdone = rdone, h1done = rdone + 32, wperm = trbuf;

    const int warp = __shfl_sync(0xffffffffu, threadIdx.x >> 5, 0), wg = warp >> 2;
    const int rank = blockIdx.x & 1;
    const int cl = blockIdx.x >> 1;
    const int r7 = ((cl - 36) * 37) >> 8;
    const int qp = cl < 36 ? (cl < 4 ? 0 : (cl - 4) & 7) : cl - 35 - 7 * r7;
    const int grp = cl < 4 ? cl + 4 : cl < 36 ? (cl - 4) >> 3 : r7 + 4;
    const bool helper = blockIdx.x >= N_MAIN;
    const int qt = helper ? (blockIdx.x - N_MAIN) * 4 : qp * 2 + rank;

    auto load_x = [&](int w, int i, int tile) {
        const uint32_t bar = xfull + (w * 5 + i) * 8;
        mbar_expect_tx(bar, 16384);
        tma_3d(ring + (i == 4 ? 2 : 3 + i) * TILE_BYTES + w * 16384, &tm_x, bar, 0, tile * 128 + w * 64, i == 0 ? 8 : 2 * i - 2);
    };
    if (warp == 4) {
        if (elect_one()) {
#pragma unroll
            for (int i = 0; i < 10; i++) mbar_init(xfull + 8 * i, 1);
#pragma unroll
            for (int i = 0; i < XN; i++) load_x(i & 1, i >> 1, qt);
            asm volatile("fence.mbarrier_init.release.cluster;" ::: "memory");
        }
        __syncwarp();
    }
    PT(6);
    if ((ring & 0xFFFFFFu) != RING_OFFSET) return;
    PT(7);
    if (warp >= 5 && elect_one()) {
        if (warp == 5) {
#pragma unroll
            for (int i = 0; i < NSLOT; i++) { mbar_init(full + 8 * i, 1); mbar_init(empty + 8 * i, 16); }
            mbar_arrive(full + 16);
            mbar_arrive(full + 24);
        } else if (warp == 6) {
#pragma unroll
            for (int i = 0; i < 6; i++) mbar_init(rdone + 8 * i, helper ? 8 : 4);
        } else if (warp == 7) {
            mbar_init(vacant, 8); mbar_init(routed, 32); mbar_init(xgfull, 1); mbar_init(gated, 8); mbar_init(soon, 1);
            mbar_init(qfull, 1); mbar_init(epv, 1); mbar_init(alldone, 8);
        } else if (warp == 8) {
            asm volatile("prefetch.tensormap [%0];" ::"l"(&tm_wq) : "memory");
        } else {
#pragma unroll
            for (int i = 0; i < 6; i++) mbar_init(rfull + ((warp - 9) * 6 + i) * 8, helper && warp == 10 ? 4 : 1);
        }
        asm volatile("fence.mbarrier_init.release.cluster;" ::: "memory");
    }
    __syncwarp();
    PT(1);
    asm volatile("barrier.cluster.arrive.relaxed.aligned;" ::: "memory");
    if (warp == 4) {
        if (elect_one()) {
#pragma unroll
            for (int i = XN; i < 10; i++) load_x(i & 1, i >> 1, qt);
        }
        __syncwarp();
    }

    if (wg == 2) {
        asm volatile("setmaxnreg.dec.sync.aligned.u32 24;");
        asm volatile("barrier.cluster.wait.aligned;" ::: "memory");
        uint32_t lane;
        asm volatile("mov.u32 %0, %%laneid;" : "=r"(lane));
        PT(2);
        if (warp == 8 && helper) {
          if (elect_one()) {
#pragma unroll 1
            for (int t = 0; t < 4; t++) {
#pragma unroll 1
                for (int i = 0; i < 20; i++) {
                    const int s = i % 3;
                    mbar_wait(empty + 8 * s, ((t + (i + 1) / 3) & 1) ^ 1);
                    mbar_expect_tx(full + 8 * s, TILE_BYTES);
                    tma_2d_mc(ring + s * TILE_BYTES + rank * 16384, &tm_wq, full + 8 * s, (((i / 5) * 2 + rank) * 4 + 3) * 128 + 64,
                              ((i + 4) % 5) * 128);
                    if (t == 0 && i == 2) {
                        asm volatile("nanosleep.u32 1500;");
#pragma unroll 1
                        for (int k = 3 + ((blockIdx.x >> 1) & 1); k < 20; k += 2) tma_prefetch(&tm_wq, (((k / 5) * 2 + rank) * 4 + 3) * 128 + 64, ((k + 4) % 5) * 128);
                    }
                    if (i == 2 && t < 3) {
#pragma unroll 1
                        for (int k = 2; k < 8; k++) load_x(k & 1, k >> 1, qt + t + 1);
                    }
                    if (i == 18 && t < 3) {
                        mbar_wait(empty + 24, t & 1);
                        load_x(0, 0, qt + t + 1); load_x(1, 0, qt + t + 1);
                    }
                }
                if (t < 3) {
                    mbar_wait(empty + 16, t & 1);
                    mbar_arrive(full + 16);
                    load_x(0, 4, qt + t + 1); load_x(1, 4, qt + t + 1);
                }
            }
            const int e = blockIdx.x - N_MAIN, nb = e == N_MOE - 1 ? 6 : 7, nkt = (nb + 1) >> 1;
            mbar_wait(h1done, 0);
            uint32_t s = 0, ph = 1;
#pragma unroll 1
            for (int o0 = 0, w; o0 < nb + 5; o0 += w) {
                const bool up = o0 < nb;
                w = o0 + 1 < (up ? nb : nb + 5) ? 2 : 1;
#pragma unroll 1
                for (int k = 0; k < (up ? 5 : nkt) * w; k++) {
                    const int o = o0 + (k & (w - 1)), i = k >> (w - 1);
                    mbar_wait(fempty + 8 * s, ph);
                    mbar_expect_tx(ffull + 8 * s, TILE_BYTES);
                    const int c0 = up ? (e * 7 + o) * 64 : (o - nb) * 128, c1 = (up ? 0 : e * 448) + i * 128;
                    tma_2d(ring + s * TILE_BYTES, up ? &tm_g : &tm_d, ffull + 8 * s, c0, c1);
                    tma_2d(ring + s * TILE_BYTES + 16384, up ? &tm_u : &tm_d, ffull + 8 * s, up ? c0 : c0 + 64, c1);
                    if (++s == FSLOT) { s = 0; ph ^= 1; }
                }
            }
          }
        } else if (warp == 8) {
          if (elect_one()) {
            PT(3);
            auto coords = [&](int i, const CUtensorMap*& tm, int& c0, int& c1) {
                c0 = rank * 64;
                if (i < 20) {
                    const int ps = i / 5;
                    tm = &tm_wq; c1 = (i % 5 < 3 ? i % 5 : 7 - i % 5) * 128;
                    if (ps == 1) {
                        c0 = 0;
                        c1 = (i == 5 ? rank : i == 6 ? 2 : 4 - rank) * 128;
                    }
                    c0 += (grp * 4 + (ps < 2 ? 2 + ps : 3 - ps)) * 128;
                } else if (i < 148) {
                    const int u = i - 20;
                    const bool isk = (u == 0) || ((u & 1) && u != 127);
                    const int b = isk ? (u + 1) >> 1 : (u == 127 ? 63 : (u >> 1) - 1);
                    tm = isk ? &tm_k : &tm_v; c1 = (grp * 64 + b) * 128;
                } else {
                    tm = &tm_wo; c0 = (i < 152 ? ((i - 132) >> 1) ^ (grp >> 2) : (grp + ((i - 150) >> 1)) & 7) * 64; c1 = (grp * 4 + (i & 1) * 2 + rank) * 128;
                }
            };
#pragma unroll 1
            for (int i = 0; i < 168; i++) {
                const CUtensorMap* tm;
                int c0, c1;
                if (i == 8) i = 10;
                const int a = i < 8 ? i : i - 2;
                const int s = i < 20 ? a % 3 : (i & 3);
                const uint32_t ph = i < 20 ? ((a + 1) / 3) & 1 : ((i >> 2) & 1) ^ (s < 2);
                coords(i, tm, c0, c1);
                if (i == QAT) mbar_wait(qfull, 0);
                mbar_wait(empty + 8 * s, ph ^ 1);
                if (i == 6) {
                    mbar_expect_tx(full + 8 * s, TILE_BYTES / 2);
                    if (rank == 0) tma_2d_mc(ring + s * TILE_BYTES, tm, full + 8 * s, c0, c1);
                } else {
                    mbar_expect_tx(full + 8 * s, TILE_BYTES);
                    tma_2d_mc(ring + s * TILE_BYTES + rank * 16384, tm, full + 8 * s, c0, c1);
                }
                if (i == 140) mbar_arrive(soon);
                if (i >= 163 && i < 167) {
                    if (i == 163) {
                        TL(0);
                        mbar_wait(routed, 0);
                        asm volatile("fence.proxy.async.global;" ::: "memory");
                        TL(1);
                        mbar_expect_tx(xgfull, TILE_BYTES);
                    }
                    asm volatile("cp.async.bulk.shared::cluster.global.mbarrier::complete_tx::bytes [%0], [%1], 8192, [%2];"
                                 ::"r"(stash + 3 * 16384 + (i - 163) * 8192), "l"(sc->gate + blockIdx.x * 2560 + (i - 163) * 512), "r"(xgfull) : "memory");
                }
                if (i == 12) asm volatile("prefetch.tensormap [%0];\nprefetch.tensormap [%1];" ::"l"(&tm_k), "l"(&tm_v) : "memory");
                if (i == 140) asm volatile("prefetch.tensormap [%0];" ::"l"(&tm_wo) : "memory");
                if (i >= GPF && i < GPF + 10)
                    asm volatile("cp.async.bulk.prefetch.L2.global [%0], 4096;" ::"l"(sc->gate + blockIdx.x * 2560 + (i - GPF) * 256) : "memory");
                const int j = i < 2 ? 2 + i : i == 2 ? 4 + ((qp - 4) & 7) : i + 9;
                if (j < 168 && (j & 7) == qp && (j & ~1) != 8) {
                    coords(j, tm, c0, c1);
                    tma_prefetch(tm, c0, c1);
                }
            }
            sc->epoch[blockIdx.x] += 1;
          }
        } else if (warp == 9) {
            const uint32_t ep = sc->epoch[blockIdx.x] + 1;
            if (helper) {
#pragma unroll 1
                for (int t = 0; t < 4; t++) {
                    if (t == 3) {
                        mbar_wait_sleep(qdone + 40, 0);
                        if (lane == 0) flag_set(sc->flag_r + (blockIdx.x - N_MAIN), ep);
                    }
                    mbar_wait_sleep(qdone + 8 * t, 0);
                    if (lane == 0) flag_set(sc->flag_q + qt + t, ep);
                }
                if (lane == 0) sc->epoch[blockIdx.x] = ep;
            } else {
                mbar_wait_sleep(gated, 0);
                flag_wait_bounded<300>(sc->flag_q + qt, ep);
                asm volatile("fence.proxy.async.global;" ::: "memory");
                if (lane == 0) mbar_expect_tx(qfull, 16384);
                __syncwarp();
                if (lane < 8)
                    asm volatile("cp.async.bulk.shared::cluster.global.mbarrier::complete_tx::bytes [%0], [%1], 2048, [%2];"
                                 ::"r"(stash + 2 * TILE_BYTES + lane * 4096 + 2048),
                                   "l"(sc->qoff + ((qt * 4 + (grp >> 1)) * 8 + lane) * 256 + (grp & 1) * 128), "r"(qfull) : "memory");
            }
            mbar_wait_bounded(alldone, 0);
        } else if (helper) {
        } else if (warp == 10) {
            const uint32_t ep = sc->epoch[blockIdx.x] + 1;
            if (lane == 0) {
                asm volatile("st.shared.u32 [%0], %1;" ::"r"(epoch), "r"(ep) : "memory");
                mbar_arrive(epv);
            }
            mbar_wait_sleep(gated, 0);
            flag_wait<400>(sc->flag_u + (lane & 3), ep);
            __syncwarp();
            const int rrow = __ldcg(sc->idx + (lane & 7));
            uint32_t hit = __ballot_sync(0xffffffffu, lane < 8 && (rrow >> 7) == qt);
            while (hit) {
                const int k = __ffs(hit) - 1, row = __shfl_sync(0xffffffffu, rrow, k);
                hit &= hit - 1;
#pragma unroll 1
                for (int i = lane; i < 40; i += 32) {
                    const int th = ((row >> 4) & 7) * 32 + (row & 7) * 4 + (i & 3);
                    ((uint32_t*)sc->gate)[(((blockIdx.x * 5 + (i >> 3)) * 2 + 1) * 256 + th) * 4 + ((i >> 1) & 2) + ((row >> 3) & 1)] =
                        __ldcg((const uint32_t*)sc->routed + k * (DM / 2) + (i < 32 ? grp * 32 + i : 224 + grp * 8 + i));
                }
            }
            mbar_arrive(routed);
        } else if (warp == 11) {
            const uint32_t ep = sc->epoch[blockIdx.x] + 1;
            const uint32_t unit = lane < 16 ? lane >> 3 : (lane >> 1) - 6;
            const uint32_t ofs = (lane & 1) * 8192 + (lane < 16 ? ((lane >> 1) & 3) * 2048 : 0);
            if (lane < 18) mbar_expect_tx(rfull + 8 * lane, 8192);
            mbar_wait_sleep(soon, 0);
            uint32_t done = lane >= 30;
            do {
                if (!done) {
                    uint4 v;
                    asm volatile("ld.relaxed.gpu.global.v4.u32 {%0, %1, %2, %3}, [%4];" : "=r"(v.x), "=r"(v.y), "=r"(v.z), "=r"(v.w)
                                 : "l"(sc->flag + (qt * 8 + grp) * 32 + lane) : "memory");
                    uint32_t ok = v.x == ep && v.y == ep && v.z == ep && v.w == ep;
                    if (ok)
                        asm volatile("{\n.reg .pred p;\nmbarrier.test_wait.parity.shared::cta.b64 p, [%1], 0;\nselp.u32 %0, 1, 0, p;\n}\n"
                                     : "=r"(ok) : "r"(unit >= 6 ? rdone + (lane - 24) * 8 : vacant) : "memory");
                    done = ok;
                    if (ok)
                        asm volatile("cp.async.bulk.shared::cluster.global.mbarrier::complete_tx::bytes [%0], [%1], %2, [%3];"
                                     ::"r"(stash + (unit >= 6 ? unit - 6 : unit) * 16384 + ofs),
                                       "l"((const char*)sc->part + ((qt * 8 + grp) * 9 + unit) * 16384 + ofs), "r"(lane < 16 ? 2048 : 8192),
                                       "r"(rfull + 16 * unit + 8 * (lane & 1)) : "memory");
                }
            } while (!__all_sync(0xffffffffu, done));
        }
    } else {
        asm volatile("setmaxnreg.inc.sync.aligned.u32 240;");
        const uint32_t lane = threadIdx.x & 31;
        PT(2);
        asm volatile("barrier.cluster.wait.aligned;" ::: "memory");
        PT(3);
        const int my_bar = 1 + wg, other_bar = 2 - wg;
        const uint32_t my_stash = stash + warp * 4096 + lane * 16;
        constexpr uint32_t T16 = TILE_BYTES / 16;
        constexpr uint32_t ring16 = RING_OFFSET >> 4;
        uint32_t rel = 0;
        if (lane < 2)
            asm("mapa.shared::cluster.u32 %0, %1, %2;" : "=r"(rel) : "r"(empty), "r"(lane));
        rel = opaque(rel);

        const int zero = gridDim.y - 1;
        PT(4);

        uint32_t q[32];
        float acc[64];
        float wsum;
        uint32_t ep_tag;
        uint2 st0, st1;
        auto project = [&](auto helper_c, int job) {
            constexpr bool HELPER = decltype(helper_c)::value;
            float (&acc32)[32] = *reinterpret_cast<float (*)[32]>(&acc[0]);
            const int tile = qt + job;
            uint32_t lane = threadIdx.x & 31;
            if (HELPER) asm volatile("mov.u32 %0, %%laneid;" : "=r"(lane));
            uint32_t xa[128];
            const uint32_t lm_off = wg * 16384 + ((warp & 3) * 16 + (lane & 15)) * 128 + (((lane >> 4) ^ (lane & 7)) << 4);
            float sm[4][4] = {}, sq[4][4] = {};
            constexpr uint32_t ONES = 0x3f803f80u;
            constexpr float SC = 0.08838834764831845f * 1.4426950408889634f;
            auto squares = [&](const uint32_t* a) {
#pragma unroll
                for (int r = 0; r < 4; r++) hmma8(sq[r], a[r & 2], a[(r & 2) + 1], a[r]);
            };
            const int row = tile * 128 + warp * 16 + (lane >> 2);
            auto load_stats = [&](int t) {
                asm volatile("ld.relaxed.gpu.global.v2.u32 {%0, %1}, [%4];\nld.relaxed.gpu.global.v2.u32 {%2, %3}, [%4 + 64];"
                             : "=r"(st0.x), "=r"(st0.y), "=r"(st1.x), "=r"(st1.y) : "l"(sc->stat + t * 128 + warp * 16 + (lane >> 2)) : "memory");
            };
            uint32_t mm0, mm1;
            float rd0, rd1;
            if (HELPER && job == 0) load_stats(tile);
#pragma unroll
            for (int i = 0; i < 5; i++) {
                mbar_wait(xfull + (wg * 5 + i) * 8, HELPER ? job & 1 : 0);
                if (i == 0) PT(5);
                if (HELPER && i == 0) TR(20 + job * 8);
                if (HELPER && i == 4) TR(20 + job * 8 + 7);
                if (HELPER && job == 1) TR(110 + i);
                const uint32_t base = ring + (i == 4 ? 2 : 3 + i) * TILE_BYTES + lm_off;
                uint32_t* a = xa + (i == 0 ? 96 : 32 * (i - 1));
#pragma unroll
                for (int ks = 0; ks < 8; ks++)
                    ldsm4((base ^ ((ks & 3) << 5)) + (ks >> 2) * 8192, a[4 * ks], a[4 * ks + 1], a[4 * ks + 2], a[4 * ks + 3]);
                if (i == 4) PT(9);
                uint32_t wb[16];
#pragma unroll
                for (int ks = 0; ks < 8; ks++) {
                    wb[2 * ks] = ONES; wb[2 * ks + 1] = ONES;
                    if (HELPER)
                        asm volatile("ld.shared.v2.u32 {%0, %1}, [%2];" : "=r"(wb[2 * ks]), "=r"(wb[2 * ks + 1]) : "r"(wperm + (lane & 3) * 8 + ((i == 0 ? 32 : 8 * i - 8) + ks) * 32));
                }
#pragma unroll
                for (int ks = 0; ks < 8; ks++) {
                    hmma(sm[ks & 3], a[4 * ks], a[4 * ks + 1], a[4 * ks + 2], a[4 * ks + 3], wb[2 * ks], wb[2 * ks + 1]);
                    if (!HELPER && i < 4) squares(a + 4 * ks);
                }
                if (HELPER && i == 0) {
                    while (__any_sync(0xffffffffu, ((st0.x ^ ep_tag) | (st1.x ^ ep_tag)) >> 16)) load_stats(tile);
                    mm0 = __byte_perm(st0.x, 0, 0x1010); mm1 = __byte_perm(st1.x, 0, 0x1010);
#pragma unroll
                    for (int ks = 0; ks < 8; ks++)
                        stsm4((base ^ ((ks & 3) << 5)) + (ks >> 2) * 8192, bf2_sub(a[4 * ks], mm0), bf2_sub(a[4 * ks + 1], mm1),
                              bf2_sub(a[4 * ks + 2], mm0), bf2_sub(a[4 * ks + 3], mm1));
                    asm volatile("fence.proxy.async.shared::cta;" ::: "memory");
                }
            }
            release_at<16>(rel);
            sched_fence(zero);
            const float m0 = ((sm[0][0] + sm[1][0]) + (sm[2][0] + sm[3][0])) * (HELPER ? 1.f : 1.f / DM);
            const float m1 = ((sm[0][2] + sm[1][2]) + (sm[2][2] + sm[3][2])) * (HELPER ? 1.f : 1.f / DM);
            if (HELPER) {
                const float id0 = __uint_as_float(st0.y), id1 = __uint_as_float(st1.y);
                rd0 = SC * id0; rd1 = SC * id1;
                if ((lane & 3) == 0) {
                    sc->r[row] = bf_round((m0 - bf_lo(mm0) * wsum) * id0);
                    sc->r[row + 8] = bf_round((m1 - bf_lo(mm1) * wsum) * id1);
                }
                __syncwarp();
                if (job == 3 && lane == 0) mbar_arrive(qdone + 40);
            } else {
                mm0 = pack_bf16(m0, m0); mm1 = pack_bf16(m1, m1);
            }
            auto centre = [&](int kt) {
#pragma unroll
                for (int i = 32 * kt; i < 32 * kt + 32; i++) asm volatile("sub.rn.bf16x2 %0, %0, %1;" : "+r"(xa[i]) : "r"((i & 1) ? mm1 : mm0));
            };
            if (EARLYA == 1 && !HELPER && wg == 1) bar_arrive(1);
            if (!HELPER) {
#pragma unroll
                for (int ks = 0; ks < 8; ks++) squares(xa + 96 + 4 * ks);
            }
            if (EARLYA == 2 && !HELPER && wg == 1) bar_arrive(1);
            if (!HELPER) centre(0);
            if ((EARLYA == 0 || HELPER) && wg == 1) bar_arrive(1);
            auto diag = [&](int r, int h) { return (lane & 4) ? sq[r][h + 1] + sq[r + 2][h + 1] : sq[r][h] + sq[r + 2][h]; };
            auto spread = [&](float v) { return __shfl_sync(0xffffffffu, v, (lane & ~3u) | (lane >> 3)) * (1.f / DM); };
            if (!HELPER) { rd0 = diag(0, 0); rd1 = diag(1, 2); }
            PT(10);

            if (HELPER) TR(20 + job * 8 + 1);
            uint32_t qs = 0, qph = HELPER ? job & 1 : 0;
            uint4 gx;
            if (HELPER) {
#pragma unroll
                for (int i = 0; i < 64; i++) acc[i] = 0.f;
            }
            const uint32_t xs16 = ring16 + 3 * T16 + wg * 1024;
            constexpr int SS = HELPER ? 0 : 3;
            auto finish_stats = [&] {
                float v0 = spread(rd0) - m0 * m0, v1 = spread(rd1) - m1 * m1;
                if (__any_sync(0xffffffffu, !(m0 * m0 <= 256.f * v0 && m1 * m1 <= 256.f * v1))) {
                    const uint4* xr = (const uint4*)x + row * (DM / 8) + (lane & 3);
                    v0 = 0.f; v1 = 0.f;
#pragma unroll 1
                    for (int i = 0; i < DM / 32; i++) {
                        const uint4 a = __ldg(xr + 4 * i), b = __ldg(xr + DM + 4 * i);
                        const uint32_t w[8] = {a.x, a.y, a.z, a.w, b.x, b.y, b.z, b.w};
#pragma unroll
                        for (int k = 0; k < 8; k++) {
                            const uint32_t d = bf2_sub(w[k], k < 4 ? mm0 : mm1);
                            float& v = k < 4 ? v0 : v1;
                            v = fmaf(bf_lo(d), bf_lo(d), fmaf(bf_hi(d), bf_hi(d), v));
                        }
                    }
#pragma unroll
                    for (int d = 1; d <= 2; d <<= 1) { v0 += __shfl_xor_sync(0xffffffffu, v0, d); v1 += __shfl_xor_sync(0xffffffffu, v1, d); }
                    v0 *= 1.f / DM; v1 *= 1.f / DM;
                    const float e0 = m0 - bf_lo(mm0), e1 = m1 - bf_lo(mm1);
                    v0 -= e0 * e0; v1 -= e1 * e1;
                }
                const float id0 = inv_den(fmaxf(v0, 0.f)), id1 = inv_den(fmaxf(v1, 0.f));
                rd0 = SC * id0; rd1 = SC * id1;
                if (warp == grp) {
                    mbar_wait(epv, 0);
                    uint32_t tg;
                    asm volatile("ld.shared.u32 %0, [%1];" : "=r"(tg) : "r"(epoch));
                    if ((lane & 3) == 0)
                        asm volatile("st.relaxed.gpu.global.v2.u32 [%0], {%1, %2};\nst.relaxed.gpu.global.v2.u32 [%0 + 64], {%3, %4};"
                                     ::"l"(sc->stat + row), "r"(__byte_perm(mm0, tg, 0x5410)), "f"(id0), "r"(__byte_perm(mm1, tg, 0x5410)), "f"(id1) : "memory");
                }
            };
#pragma unroll 1
            for (int pass = 0;; pass++) {
                const uint32_t hs = my_stash + (pass == 2 ? 0 : pass + 1) * TILE_BYTES;
                uint4* const dst = sc->qoff + ((tile * 4 + pass) * 8 + warp) * 256 + lane;
                auto put = [&](int lo) {
#pragma unroll
                    for (int i = lo; i < lo + 4; i++) {
                        const uint4 v = make_uint4(pack_bf16(acc[8 * i] * rd0, acc[8 * i + 1] * rd0), pack_bf16(acc[8 * i + 2] * rd1, acc[8 * i + 3] * rd1),
                                                   pack_bf16(acc[8 * i + 4] * rd0, acc[8 * i + 5] * rd0), pack_bf16(acc[8 * i + 6] * rd1, acc[8 * i + 7] * rd1));
                        if (HELPER) dst[i * 32] = v;
                        else sts128(hs + i * 512, v.x, v.y, v.z, v.w);
                        if (PUTF == 0 ? (i == 2 || i == 5) : PUTF == 1 ? (i == 3) : PUTF == 2 ? (i & 1) : false) sched_fence(zero);
                    }
                };
                auto gate_load = [&](int j) {
                    const uint32_t* src = (const uint32_t*)x + (qt * 128 + warp * 16 + (lane >> 2)) * (DM / 2) + (lane & 3) +
                                          (j < 4 ? grp * 32 + j * 8 : 256 + grp * 8);
                    asm volatile("ld.global.nc.u32 %0, [%4];\nld.global.nc.u32 %1, [%4 + %5];\n"
                                 "ld.global.nc.u32 %2, [%4 + 16];\nld.global.nc.u32 %3, [%4 + %5 + 16];"
                                 : "=r"(gx.x), "=r"(gx.y), "=r"(gx.z), "=r"(gx.w) : "l"(src), "n"(8 * DM * 2));
                };
                auto gate_store = [&](int j) {
                    const float id0 = rd0 * (1.f / SC), id1 = rd1 * (1.f / SC);
                    uint4* g = sc->gate + (blockIdx.x * 5 + j) * 512 + threadIdx.x;
                    g[0] = gx;
                    g[256] = make_uint4(silu2_ln(normalise(gx.x, mm0, id0)), silu2_ln(normalise(gx.y, mm1, id1)),
                                        silu2_ln(normalise(gx.z, mm0, id0)), silu2_ln(normalise(gx.w, mm1, id1)));
                };
                auto advance = [&] {
                    const uint32_t r = rel ? rel + 8 * qs : 0;
                    if (++qs == 2) qph ^= 1;
                    if (qs == 3) qs = 0;
                    return r;
                };
                if (!HELPER && pass == 1) {
#pragma unroll
                    for (int turn = 0; turn < 3; turn++) {
                        if (turn) mbar_wait(full + 8 * qs, qph);
                        bar_sync(my_bar);
                        const uint32_t tile16 = ring16 + qs * T16;
                        wg_fence();
#pragma unroll
                        for (int ks = 0; ks < (turn == 1 ? 8 : 16); ks++) {
                            const uint32_t* a = xa + (turn == 2 ? 64 : turn * 64) + 4 * ks;
                            if (turn == 2 && ks < 8) wgmma_ss64(acc32, desc_kmajor(xs16 - (ks >> 2) * 512, ks), desc_nmajor(tile16, ks), 1);
                            else wgmma_rs64(acc32, a[0], a[1], a[2], a[3], desc_nmajor(tile16, ks), turn || ks);
                        }
                        wg_commit();
                        bar_arrive(other_bar);
                        const uint32_t rl = advance();
                        if (turn == 2) mbar_wait(full + 8 * qs, qph);
                        wg_wait<0>();
                        TA(5 + 2 * turn);
                        release_at<0>(rl);
                    }
                    pin(acc32);
                    put(0);
                    continue;
                }
                uint32_t rl = 0;
#pragma unroll
                for (int kt = 0; kt < 5; kt++) {
                    const bool takes = !HELPER || kt == 0 || kt == 2 || kt == 3, passes = !HELPER || kt == 1 || kt == 2 || kt == 4;
                    if (kt != 0 || pass == 0) mbar_wait(full + 8 * qs, qph);
                    if (takes) bar_sync(my_bar);
                    const uint32_t tile16 = ring16 + qs * T16;
                    wg_fence();
                    if (kt != SS) {
                        mma_tile<1>(acc, xa + (kt < SS ? kt : kt - 1) * 32, tile16, kt != 0);
                    } else {
#pragma unroll
                        for (int ks = 0; ks < 8; ks++) wgmma_ss(acc, desc_kmajor(xs16 - (ks >> 2) * 512, ks), desc_nmajor(tile16, ks), kt || ks);
                        wg_commit();
                    }
                    if (passes && !(HELPER && kt == 4 && pass == 3 && wg == 1)) bar_arrive(other_bar);
                    if (HELPER && pass == 0 && kt < 4) centre(kt);
                    if (!HELPER && pass == 0 && kt < 3) {
#pragma unroll
                        for (int ks = 3 * kt; ks < 3 * kt + 3 && ks < 8; ks++) {
                            const uint32_t ad = ((ring + 3 * TILE_BYTES + lm_off) ^ ((ks & 3) << 5)) + (ks >> 2) * 8192;
                            uint32_t a, b, c, d;
                            ldsm4(ad, a, b, c, d);
                            stsm4(ad, bf2_sub(a, mm0), bf2_sub(b, mm1), bf2_sub(c, mm0), bf2_sub(d, mm1));
                        }
                        if (kt == 2) asm volatile("fence.proxy.async.shared::cta;" ::: "memory");
                    }
                    if (!HELPER && pass == 0 && kt == FINK) finish_stats();
                    if (HELPER && kt == 2 && pass == 3 && job < 3) load_stats(tile + 1);
                    if (!HELPER && pass >= 2 && kt < 4) {
                        if (kt & 1) gate_store((pass - 2) * 2 + (kt >> 1));
                        else gate_load((pass - 2) * 2 + (kt >> 1));
                    }
                    if (!HELPER && pass == G4 && kt == 3) gate_load(4);
                    if (!HELPER && pass == G4 && kt == 4) gate_store(4);
                    const uint32_t rl_prev = rl;
                    rl = advance();
                    if (!passes) continue;
                    if (HELPER && kt != 2) {
                        wg_wait<1>();
                        if (job == 1) TR(120 + pass * 5 + kt - 1);
                        release_at<0>(rl_prev);
                        if (kt == 1 && pass == 3) release_at<24>(rel);
                    }
                    if (kt == 4 && !(HELPER && pass == 3)) mbar_wait(full + 8 * qs, qph);
                    wg_wait<0>();
                    if (!HELPER) TA(pass * 5 + kt);
                    if (HELPER && job == 1) TR(120 + pass * 5 + kt);
                    release_at<0>(rl);
                    if (!HELPER && kt < 3 && pass == 0) centre(kt + 1);
                }
                pin(acc);
                if (!HELPER && pass == 3) break;
                put(0);
                put(4);
                if (HELPER) TR(20 + job * 8 + 2 + pass);
                if (HELPER && pass == 3) {
                    __syncwarp();
                    if (lane == 0) mbar_arrive(qdone + 8 * job);
                    return;
                }
            }
            release_at<24>(rel);
            if (lane == 0) mbar_arrive(gated);
#pragma unroll
            for (int i = 0; i < 32; i++) {
                const float r = (i & 1) ? rd1 : rd0;
                q[i] = pack_bf16(acc[2 * i] * r, acc[2 * i + 1] * r);
            }
        };
        if (helper) {
            const uint32_t ep = sc->epoch[blockIdx.x] + 1;
            if (threadIdx.x < 160) {
                const uint32_t* w32 = (const uint32_t*)wr + (threadIdx.x >> 2) * 8 + (threadIdx.x & 3);
                asm volatile("st.shared.v2.u32 [%0], {%1, %2};" ::"r"(wperm + threadIdx.x * 8), "r"(__ldg(w32)), "r"(__ldg(w32 + 4)) : "memory");
            }
            asm volatile("bar.sync 3, 256;" ::: "memory");
            float ws[4] = {};
#pragma unroll 4
            for (int ks = 0; ks < 40; ks++) {
                uint32_t b0, b1;
                asm volatile("ld.shared.v2.u32 {%0, %1}, [%2];" : "=r"(b0), "=r"(b1) : "r"(wperm + (lane & 3) * 8 + ks * 32));
                hmma(ws, 0x3f803f80u, 0x3f803f80u, 0x3f803f80u, 0x3f803f80u, b0, b1);
            }
            wsum = ws[0];
            ep_tag = ep << 16;
            TR(0);
#pragma unroll 1
            for (int job = 0; job < 4; job++) {
                project(cint<1>(), job);
                TR(1 + job);
            }
            if (elect_one()) mbar_arrive(h1done);
            ffn_role(sc, ring, ffull, fempty, alldone, blockIdx.x - N_MAIN, ep, warp, x);
            return;
        }
        project(cint<0>(), 0);
        TRM(2);
        TG(112);

        float o[64];
        uint32_t p[32];
        float l0, l1;
        constexpr float L_LO = 9.313225746154785e-10f, L_HI = 1.152921504606847e18f;
        float l_hi = L_HI;
        float (&s)[64] = acc;

        auto exp_range = [&](const float (&s)[64], int lo, int hi, float& u0, float& u1) {
            float w0 = 0.f, w1 = 0.f;
#pragma unroll
            for (int i = lo; i < hi; i += 4) {
                const float e0 = ex2(s[i]), e1 = ex2(s[i + 1]), e2 = ex2(s[i + 2]), e3 = ex2(s[i + 3]);
                u0 += e0; u1 += e2;
                if (i == lo) { w0 = e1; w1 = e3; } else { w0 += e1; w1 += e3; }
                p[i / 2] = pack_bf16(e0, e1); p[i / 2 + 1] = pack_bf16(e2, e3);
            }
            u0 += w0; u1 += w1;
        };
        auto unsafe = [&](bool first, float u0, float u1) {
            return (bool)__any_sync(0xffffffffu, !(u0 + u1 <= l_hi) || (first && !(fminf(u0, u1) >= L_LO)));
        };
        auto softmax_true_max = [&](const float (&s)[64], bool first, float b0, float b1, float& u0, float& u1) {
            uint32_t t;
            asm volatile("mov.u32 %0, %%tid.x;" : "=r"(t));
            uint4* const st = sc->rare + blockIdx.x * (17 * 256) + t;
            auto ld = [](const uint4* a) {
                uint4 v;
                asm volatile("ld.global.v4.u32 {%0, %1, %2, %3}, [%4];" : "=r"(v.x), "=r"(v.y), "=r"(v.z), "=r"(v.w) : "l"(a) : "memory");
                return v;
            };
#pragma unroll
            for (int i = 0; i < 16; i++)
                asm volatile("st.global.v4.f32 [%0], {%1, %2, %3, %4};" ::"l"(st + i * 256), "f"(s[4 * i]), "f"(s[4 * i + 1]), "f"(s[4 * i + 2]), "f"(s[4 * i + 3]) : "memory");
            float a0 = s[0], a1 = s[2];
#pragma unroll 1
            for (int i = 0; i < 16; i++) {
                const uint4 v = ld(st + i * 256);
                a0 = fmaxf(a0, fmaxf(__uint_as_float(v.x), __uint_as_float(v.y)));
                a1 = fmaxf(a1, fmaxf(__uint_as_float(v.z), __uint_as_float(v.w)));
            }
            float t0 = b0, t1 = b1, sg0 = 0.f, sg1 = 0.f;
            if (l_hi < 0.f) {
                const uint4 v = ld(st + 16 * 256);
                sg0 = __uint_as_float(v.x); sg1 = __uint_as_float(v.y);
            }
#pragma unroll
            for (int d = 1; d <= 2; d <<= 1) {
                a0 = fmaxf(a0, __shfl_xor_sync(0xffffffffu, a0, d)); a1 = fmaxf(a1, __shfl_xor_sync(0xffffffffu, a1, d));
                t0 += __shfl_xor_sync(0xffffffffu, t0, d); t1 += __shfl_xor_sync(0xffffffffu, t1, d);
            }
            if (!first) {
                a0 = fmaxf(a0, l_hi < 0.f ? sg0 : __log2f(t0)); a1 = fmaxf(a1, l_hi < 0.f ? sg1 : __log2f(t1));
            }
            const float al0 = first ? 1.f : ex2(sg0 - a0), al1 = first ? 1.f : ex2(sg1 - a1);
            asm volatile("st.global.v2.f32 [%0], {%1, %2};" ::"l"(st + 16 * 256), "f"(a0), "f"(a1) : "memory");
            l_hi = -1.f;
            u0 = b0 * al0; u1 = b1 * al1;
#pragma unroll 1
            for (int i = 0; i < 16; i++) {
                const uint4 v = ld(st + i * 256);
                const float e0 = ex2(__uint_as_float(v.x) - a0), e1 = ex2(__uint_as_float(v.y) - a0);
                const float e2 = ex2(__uint_as_float(v.z) - a1), e3 = ex2(__uint_as_float(v.w) - a1);
                u0 += e0 + e1; u1 += e2 + e3;
                asm volatile("st.global.v2.u32 [%0], {%1, %2};" ::"l"((uint2*)(st + (i >> 1) * 256) + (i & 1)), "r"(pack_bf16(e0, e1)), "r"(pack_bf16(e2, e3)) : "memory");
            }
#pragma unroll
            for (int i = 0; i < 8; i++) {
                const uint4 v = ld(st + i * 256);
                p[4 * i] = v.x; p[4 * i + 1] = v.y; p[4 * i + 2] = v.z; p[4 * i + 3] = v.w;
            }
            if (&s != &o) {
#pragma unroll
                for (int i = 0; i < 64; i++) o[i] *= (i & 2) ? al1 : al0;
            }
        };
        auto inv_sums = [&](float& i0, float& i1) {
            float a = l0, b = l1;
            a += __shfl_xor_sync(0xffffffffu, a, 1); b += __shfl_xor_sync(0xffffffffu, b, 1);
            a += __shfl_xor_sync(0xffffffffu, a, 2); b += __shfl_xor_sync(0xffffffffu, b, 2);
            i0 = rcp(a); i1 = rcp(b);
        };

        {
            bar_sync(my_bar);
            wg_fence();
            mma_tile<0>(o, q, ring16, 0);
            mbar_wait(full + 8, 0);
            wg_fence();
            mma_tile<0>(s, q, ring16 + T16, 0);
            bar_arrive(other_bar);
            wg_wait<1>();
            TA(20);
            release_at<0>(rel);
            pin(o);
            l0 = 0.f; l1 = 0.f;
            exp_range(o, 0, 64, l0, l1);
            mbar_wait(full + 16, 1);
            wg_wait<0>();
            if (unsafe(true, l0, l1)) softmax_true_max(o, true, 0.f, 0.f, l0, l1);
        }
        uint32_t qsrc = my_stash;
        float il0 = 0.f, il1 = 0.f;
        auto step = [&](auto odd_c, int m) {
            constexpr int ODD = decltype(odd_c)::value;
            constexpr int KS = ODD ? 3 : 1, VS = ODD ? 0 : 2;
            constexpr int SP = ODD ? SPLITO : SPLIT;
            [[maybe_unused]] const int it = 2 * m + ODD;
            const uint32_t ph = m & 1;
            TC(0);
            bar_sync(my_bar);
            TC(1);
            if (ODD || m) {
                wg_fence();
                mma_tile<0>(s, q, ring16 + KS * T16, 0);
            }
            TC(2);
            if (!ODD) {
                if ((m & 7) == 0 && m) {
#pragma unroll
                    for (int i = FSPLIT; i < 8; i++)
                        sts128(qsrc + i * 512,
                               pack_bf16(o[8 * i] * il0, o[8 * i + 1] * il0), pack_bf16(o[8 * i + 2] * il1, o[8 * i + 3] * il1),
                               pack_bf16(o[8 * i + 4] * il0, o[8 * i + 5] * il0), pack_bf16(o[8 * i + 6] * il1, o[8 * i + 7] * il1));
                    qsrc += m == 24 ? -2 * TILE_BYTES : TILE_BYTES;
                }
                wg_fence();
            }
#pragma unroll
            for (int ks = 0; ks < 8; ks++) {
                wgmma_rs<1>(o, p[4 * ks], p[4 * ks + 1], p[4 * ks + 2], p[4 * ks + 3], desc_nmajor(ring16 + VS * T16, ks),
                            (ks == 0 && !ODD) ? ((m & 7) != 0) : 1);
                if (ks == SP / 8 - 1 || ks == 7) wg_commit();
            }
            TC(3);
            bar_arrive(other_bar);
            const bool last = ODD && (m & 7) == 7;
            if (last && INVP == 0) {
                inv_sums(il0, il1);
                l0 = 0.f; l1 = 0.f; l_hi = L_HI;
            }
            wg_wait<1>();
            TA(21 + it);
            TC(4);
            release_at<8 * KS>(rel);
            const bool newq = (m & 7) == 7;
            if (!ODD) {
                lds128_if<0>(newq, qsrc, q[0], q[1], q[2], q[3]);
                lds128_if<512>(newq, qsrc, q[4], q[5], q[6], q[7]);
                if (QB != 1) lds128_if<1024>(newq, qsrc, q[8], q[9], q[10], q[11]);
            }
            if (last && INVP == 1) {
                inv_sums(il0, il1);
                l0 = 0.f; l1 = 0.f; l_hi = L_HI;
            }
            pin(s);
            float u0 = l0, u1 = l1;
            exp_range(s, 0, SP, u0, u1);
            mbar_wait_hot(full + 8 * (KS ^ 2), ph ^ 1);
            if (!ODD) {
                if (QB == 1) lds128_if<1024>(newq, qsrc, q[8], q[9], q[10], q[11]);
                lds128_if<1536>(newq, qsrc, q[12], q[13], q[14], q[15]);
                lds128_if<2048>(newq, qsrc, q[16], q[17], q[18], q[19]);
                if (QB == 2) lds128_if<2560>(newq, qsrc, q[20], q[21], q[22], q[23]);
            }
            TC(5);
            wg_wait<0>();
            release_at<8 * VS>(rel);
            pin(o);
            exp_range(s, SP, 64, u0, u1);
            TC(6);
            mbar_wait_hot(full + 8 * (VS ^ 2), ODD ? ph : ph ^ 1);
            if (!ODD) {
                if (QB != 2) lds128_if<2560>(newq, qsrc, q[20], q[21], q[22], q[23]);
                lds128_if<3072>(newq, qsrc, q[24], q[25], q[26], q[27]);
                lds128_if<3584>(newq, qsrc, q[28], q[29], q[30], q[31]);
            } else if (last) {
#pragma unroll
                for (int i = 0; i < FSPLIT; i++)
                    sts128(qsrc + i * 512,
                           pack_bf16(o[8 * i] * il0, o[8 * i + 1] * il0), pack_bf16(o[8 * i + 2] * il1, o[8 * i + 3] * il1),
                           pack_bf16(o[8 * i + 4] * il0, o[8 * i + 5] * il0), pack_bf16(o[8 * i + 6] * il1, o[8 * i + 7] * il1));
            }
            if (unsafe(last, u0, u1)) softmax_true_max(s, last, l0, l1, u0, u1);
            l0 = u0; l1 = u1;
            TC(7);
            TF(3 + it);
        };
#pragma unroll 1
        for (int m = 0;; m++) {
            step(cint<0>(), m);
            if (m == 31) break;
            step(cint<1>(), m);
        }
        uint32_t ob[64];
        const uint32_t t128 = threadIdx.x & 127;
        uint32_t ep, tag;
        const uint32_t half = 0x8000u;
        auto send = [&](uint4* dst, const float* a) {
            asm volatile("st.relaxed.gpu.global.v4.u32 [%0], {%1, %2, %3, %4};" ::"l"(dst), "r"(lop3<0xD8>(pack_bf16(a[0], a[1]), tag, 0x10000u)),
                         "r"(pack_bf16(a[2], a[3])), "r"(pack_bf16(a[4], a[5])), "r"(pack_bf16(a[6], a[7])) : "memory");
        };
        auto hint = [&](int dst, int job) {
            asm volatile("st.relaxed.gpu.global.u32 [%0], %1;" ::"l"((uint32_t*)(sc->flag + (qt * 8 + dst) * 32 + job) + (warp & 3)), "r"(ep) : "memory");
        };
        float a32[32], own[32];
        auto half_mma = [&](const uint32_t* a, const uint32_t* b, uint32_t t16, int accumulate) {
            wg_fence();
#pragma unroll
            for (int ks = 0; ks < 8; ks++) wgmma_rs64(a32, a[4 * ks], a[4 * ks + 1], a[4 * ks + 2], a[4 * ks + 3], desc_nmajor(t16, ks), ks ? 1 : accumulate);
#pragma unroll
            for (int ks = 0; ks < 8; ks++) wgmma_rs64(a32, b[4 * ks], b[4 * ks + 1], b[4 * ks + 2], b[4 * ks + 3], desc_nmajor(t16, 8 + ks), 1);
            wg_commit();
        };
        auto block_mma = [&](uint32_t sb, uint32_t ph, bool pass_turn) {
            mbar_wait(full + 8 * sb, ph);
            bar_sync(my_bar);
            half_mma(q, ob, ring16 + sb * T16, zero);
            mbar_wait(full + 8 * sb + 8, ph);
            half_mma(ob + 32, p, ring16 + (sb + 1) * T16, 1);
            if (pass_turn) bar_arrive(other_bar);
        };
        auto send_strips = [&](int u) {
            const uint32_t t = opaque(t128);
            const int d0 = (grp & 4) ^ (4 * u);
            uint4* dst = sc->part + (((qt * 8 + d0) * 9 + u) * 2 + wg) * 512 + (grp & 3) * 128 + t;
#pragma unroll
            for (int i = 0; i < 4; i++) send(dst + i * 9 * 1024, a32 + 8 * i);
            if ((t & 31) < 4) hint(d0 + (t & 31), u * 8 + (grp & 3) * 2 + wg);
        };
        uint32_t xs[4], gs[4];
        {
            [[maybe_unused]] const int c = 9;
            TS(0);
            auto fetch_o = [&](int lo, int hi) {
#pragma unroll
                for (int i = lo; i < hi; i++)
                    lds128(qsrc + (1 + (i >> 3)) * TILE_BYTES + (i & 7) * 512, ob[4 * i], ob[4 * i + 1], ob[4 * i + 2], ob[4 * i + 3]);
            };
            fetch_o(0, 3);
            bar_sync(my_bar);
            wg_fence();
            mma_tile<1>(o, p, ring16 + 3 * T16, 1);
            sched_fence(zero);
            inv_sums(il0, il1);
            asm volatile("" : "+f"(il0), "+f"(il1));
            sched_fence(zero);
            fetch_o(3, 6);
            wg_fence();
#pragma unroll
            for (int ks = 0; ks < 8; ks++) {
                wgmma_rs64(a32, q[4 * ks], q[4 * ks + 1], q[4 * ks + 2], q[4 * ks + 3], desc_nmajor(ring16, ks), ks);
                if (ks == 3) { wg_commit(); sched_fence(zero); fetch_o(6, 8); wg_fence(); }
            }
            TS(1);
#pragma unroll
            for (int ks = 0; ks < 8; ks++) wgmma_rs64(a32, ob[4 * ks], ob[4 * ks + 1], ob[4 * ks + 2], ob[4 * ks + 3], desc_nmajor(ring16, 8 + ks), 1);
            wg_commit();
            TS(2);
            bar_arrive(other_bar);
            wg_wait<1>();
            release_at<24>(rel);
            pin(o);
#pragma unroll
            for (int i = 0; i < 32; i++) {
                const float r = (i & 1) ? il1 : il0;
                asm volatile("cvt.rn.bf16x2.f32 %0, %1, %2;" : "=r"(p[i]) : "f"(o[2 * i + 1] * r), "f"(o[2 * i] * r));
                if ((i & 7) == 7) fetch_o(8 + (i >> 3) * 2, 10 + (i >> 3) * 2);
            }
            TS(3);
            mbar_wait(full + 8, 0);
            wg_wait<0>();
            release_at<0>(rel);
            __syncwarp();
            if (lane == 0) mbar_arrive(vacant);
            TS(4);
            bar_sync(my_bar);
            half_mma(ob + 32, p, ring16 + T16, 1);
            TS(5);
            bar_arrive(other_bar);
            TRM(66);
            TG(113);
            mbar_wait(routed, 0);
            asm volatile("ld.shared.u32 %0, [%1];" : "=r"(ep) : "r"(epoch));
            tag = ep << 16;
            const uint4* src = sc->gate + (blockIdx.x * 5 + 4) * 512 + threadIdx.x;
            asm volatile("ld.global.cg.v4.u32 {%0, %1, %2, %3}, [%4];" : "=r"(xs[0]), "=r"(xs[1]), "=r"(xs[2]), "=r"(xs[3]) : "l"(src));
            asm volatile("ld.global.cg.v4.u32 {%0, %1, %2, %3}, [%4];" : "=r"(gs[0]), "=r"(gs[1]), "=r"(gs[2]), "=r"(gs[3]) : "l"(src + 256));
            sched_fence(zero);
            wg_wait<0>();
            TS(6);
            release_at<8>(rel);
            pin(a32);
            send_strips(0);
            TS(7);
        }
        uint32_t v[4][4];
        auto stale = [&]() {
            return __any_sync(0xffffffffu, lop3<0xA8>(lop3<0x7E>(v[0][0], v[1][0], tag), lop3<0x7E>(v[2][0], v[3][0], tag), 0x10000u));
        };
        auto recv = [&](int u) {
            mbar_wait(rfull + 16 * u + 8 * wg, 0);
#pragma unroll
            for (int i = 0; i < 4; i++)
                lds128(stash + (u >= 6 ? u - 6 : u) * 16384 + wg * 8192 + i * 2048 + t128 * 16, v[i][0], v[i][1], v[i][2], v[i][3]);
            if (stale()) {
                const uint4* src = sc->part + (((qt * 8 + grp) * 9 + u) * 2 + wg) * 512 + opaque(t128);
                do {
#pragma unroll
                    for (int i = 0; i < 4; i++)
                        asm volatile("ld.relaxed.gpu.global.v4.u32 {%0, %1, %2, %3}, [%4];" : "=r"(v[i][0]), "=r"(v[i][1]), "=r"(v[i][2]), "=r"(v[i][3])
                                     : "l"(src + i * 128) : "memory");
                } while (stale());
            }
            if (u < 3 && lane == 0) mbar_arrive(rdone + (u * 2 + wg) * 8);
        };
        auto accumulate = [&](float* dst, int stride) {
#pragma unroll
            for (int i = 0; i < 4; i++) {
                float* a = dst + stride * i;
                a[0] += bf_lo(v[i][0]);
                a[1] += __uint_as_float(lop3<0xEC>(v[i][0], half, 0xfffe0000u));
#pragma unroll
                for (int k = 1; k < 4; k++) { a[2 * k] += bf_lo(v[i][k]); a[2 * k + 1] += bf_hi(v[i][k]); }
            }
        };
        auto gate = [](uint32_t x2, uint32_t g2, float lo, float hi) {
            uint32_t sv = pack_bf16(lo, hi);
            asm("mul.rn.bf16x2 %0, %0, %1;" : "+r"(sv) : "r"(g2));
            asm("add.rn.bf16x2 %0, %0, %1;" : "+r"(sv) : "r"(x2));
            return sv;
        };
        uint4* const outbox = sc->part + qt * (8 * 9 * 1024) + wg * 512 + t128;
        auto step_o = [&](int f) {
            [[maybe_unused]] const int c = f;
            const uint32_t sb = (f & 1) ? 0 : 2;
            block_mma(sb, (((f + 3) >> 1) ^ f) & 1, true);
            wg_wait<1>();
            const uint32_t rl = rel && f < 7 ? rel + 8 * sb : 0;
            release_at<0>(rl);
            if (f >= 1) recv(f - 1);
            wg_wait<0>();
            TS(0);
            release_at<8>(rl);
            pin(a32);
            if (f == 0) {
                send_strips(1);
            } else {
                const int d = (grp + f) & 7;
#pragma unroll
                for (int i = 0; i < 4; i++) send(outbox + (d * 9 + f + 1) * 1024 + i * 128, a32 + 8 * i);
                if (lane == 0) hint(d, 14 + 2 * f + wg);
            }
            TS(1);
        };
        {
            float st[8] = {};
#pragma unroll 1
            for (int f = 0; f < 3; f++) {
                [[maybe_unused]] const int c = f;
                step_o(f);
                if (f >= 1) accumulate(st, 0);
                TS(2);
            }
            uint32_t w[4];
#pragma unroll
            for (int i = 0; i < 4; i++) w[i] = gate(xs[i], gs[i], st[2 * i], st[2 * i + 1]);
            const bool odd = lane & 1;
            const uint32_t r0 = __shfl_xor_sync(0xffffffffu, odd ? w[0] : w[2], 1), r1 = __shfl_xor_sync(0xffffffffu, odd ? w[1] : w[3], 1);
            uint2* dst = (uint2*)out + (qt * 128 + warp * 16 + (lane >> 2)) * (DM / 4) + 128 + grp * 4 + (lane & 1) * 2 + ((lane >> 1) & 1);
            dst[0] = odd ? make_uint2(r0, w[2]) : make_uint2(w[0], r0);
            dst[2 * DM] = odd ? make_uint2(r1, w[3]) : make_uint2(w[1], r1);
        }
#pragma unroll
        for (int i = 0; i < 32; i++) own[i] = 0.f;
#pragma unroll 1
        for (int f = 3; f < 8; f++) {
            [[maybe_unused]] const int c = f;
            step_o(f);
            accumulate(own, 8);
            TS(2);
        }
        {
            [[maybe_unused]] const int c = 8;
            recv(7);
            accumulate(own, 8);
            TS(7);
            block_mma(2, 1, wg == 0);
            TRM(71);
            TS(0);
            recv(8);
            accumulate(own, 8);
            TS(1);
            wg_wait<1>();
            uint32_t xv[16], gv[16];
            mbar_wait(xgfull, 0);
            if (lane == 0) mbar_arrive(alldone);
#pragma unroll
            for (int j = 0; j < 4; j++) {
                lds128(stash + 3 * 16384 + j * 8192 + threadIdx.x * 16, xv[4 * j], xv[4 * j + 1], xv[4 * j + 2], xv[4 * j + 3]);
                lds128(stash + 3 * 16384 + j * 8192 + 4096 + threadIdx.x * 16, gv[4 * j], gv[4 * j + 1], gv[4 * j + 2], gv[4 * j + 3]);
            }
            TS(2);
            wg_wait<0>();
            pin(a32);
#pragma unroll
            for (int i = 0; i < 32; i++) own[i] += a32[i];
            TS(3);
            const uint32_t tb = ring + warp * 2048;
#pragma unroll
            for (int j = 0; j < 4; j++)
                stsm4(tb + (lane & 15) * 128 + (((2 * j + (lane >> 4)) ^ (lane & 7)) << 4),
                      gate(xv[4 * j], gv[4 * j], own[8 * j], own[8 * j + 1]), gate(xv[4 * j + 1], gv[4 * j + 1], own[8 * j + 2], own[8 * j + 3]),
                      gate(xv[4 * j + 2], gv[4 * j + 2], own[8 * j + 4], own[8 * j + 5]), gate(xv[4 * j + 3], gv[4 * j + 3], own[8 * j + 6], own[8 * j + 7]));
            __syncwarp();
#pragma unroll
            for (int j = 0; j < 4; j++) {
                const uint32_t row = j * 4 + (lane >> 3);
                uint4 v;
                lds128(tb + row * 128 + (((lane & 7) ^ (row & 7)) << 4), v.x, v.y, v.z, v.w);
                ((uint4*)out)[(qt * 128 + warp * 16 + row) * (DM / 8) + grp * 8 + (lane & 7)] = v;
            }
        }
        TRM(73);
        TG(111);
    }
}

typedef CUresult (*EncodeFn)(CUtensorMap*, CUtensorMapDataType, cuuint32_t, void*, const cuuint64_t*, const cuuint64_t*,
                             const cuuint32_t*, const cuuint32_t*, CUtensorMapInterleave, CUtensorMapSwizzle,
                             CUtensorMapL2promotion, CUtensorMapFloatOOBfill);

void make_map(EncodeFn enc, CUtensorMap* tm, const void* ptr, uint64_t cols, uint64_t rows) {
    cuuint64_t gd[2] = {cols, rows};
    cuuint64_t gs[1] = {cols * 2};
    cuuint32_t bd[2] = {64, 128};
    cuuint32_t es[2] = {1, 1};
    enc(tm, CU_TENSOR_MAP_DATA_TYPE_BFLOAT16, 2, const_cast<void*>(ptr), gd, gs, bd, es, CU_TENSOR_MAP_INTERLEAVE_NONE,
        CU_TENSOR_MAP_SWIZZLE_128B, CU_TENSOR_MAP_L2_PROMOTION_L2_256B, CU_TENSOR_MAP_FLOAT_OOB_FILL_NONE);
}

}

extern "C" void kernel_launch(void* const* d_in, const int* in_sizes, int n_in, void* d_out, int out_size) {
    const __nv_bfloat16* x = (const __nv_bfloat16*)d_in[0];
    const __nv_bfloat16* wr = (const __nv_bfloat16*)d_in[6];
    __nv_bfloat16* out = (__nv_bfloat16*)d_out;

    EncodeFn enc = nullptr;
    cudaDriverEntryPointQueryResult qr;
    cudaGetDriverEntryPoint("cuTensorMapEncodeTiled", (void**)&enc, cudaEnableDefault, &qr);
    CUtensorMap tm_x, tm_wq, tm_k, tm_v, tm_wo, tm_g, tm_u, tm_d;
    {
        cuuint64_t gd[3] = {64, SEQ, DM / 64};
        cuuint64_t gs[2] = {DM * 2, 128};
        cuuint32_t bd[3] = {64, 64, 2};
        cuuint32_t es[3] = {1, 1, 1};
        enc(&tm_x, CU_TENSOR_MAP_DATA_TYPE_BFLOAT16, 3, d_in[0], gd, gs, bd, es, CU_TENSOR_MAP_INTERLEAVE_NONE,
            CU_TENSOR_MAP_SWIZZLE_128B, CU_TENSOR_MAP_L2_PROMOTION_L2_256B, CU_TENSOR_MAP_FLOAT_OOB_FILL_NONE);
    }
    make_map(enc, &tm_k, d_in[1], DH, (uint64_t)NH * SEQ);
    make_map(enc, &tm_v, d_in[2], DH, (uint64_t)NH * SEQ);
    make_map(enc, &tm_wq, d_in[3], NH * DH, DM);
    make_map(enc, &tm_wo, d_in[4], DM, NH * DH);
    make_map(enc, &tm_g, d_in[7], FF, DM);
    make_map(enc, &tm_u, d_in[8], FF, DM);
    make_map(enc, &tm_d, d_in[9], DM, FF);
    cudaFuncSetAttribute(fused_attn_kernel, cudaFuncAttributeMaxDynamicSharedMemorySize, SMEM_BYTES);

    Scratch* sc = nullptr;
    cudaGetSymbolAddress((void**)&sc, g_scratch);

    cudaLaunchConfig_t cfg = {};
    cfg.gridDim = dim3(N_MAIN + N_MOE);
    cfg.blockDim = dim3(384);
    cfg.dynamicSmemBytes = SMEM_BYTES;
    cfg.stream = cudaStreamPerThread;
    cudaLaunchAttribute at[1];
    at[0].id = cudaLaunchAttributeClusterDimension;
    at[0].val.clusterDim.x = 2; at[0].val.clusterDim.y = 1; at[0].val.clusterDim.z = 1;
    cfg.attrs = at; cfg.numAttrs = 1;
    cudaLaunchKernelEx(&cfg, fused_attn_kernel, x, wr, out, sc, tm_x, tm_wq, tm_k, tm_v, tm_wo, tm_g, tm_u, tm_d);
}
```

```cpp
#include <cuda_runtime.h>
#include <cuda.h>
#include <cuda_bf16.h>
#include <stdint.h>

namespace {

constexpr int SEQ = 2048, DM = 640, NH = 32, DH = 128, FF = 1728, CAP = 8;
constexpr int NSLOT = 4;
constexpr int TILE_BYTES = 32768;
constexpr uint32_t RING_OFFSET = 1024;
constexpr int SMEM_BYTES = (NSLOT + 3) * TILE_BYTES + 416 + 1408 + 96;
constexpr int N_MAIN = 128, N_MOE = 4;

struct Scratch {
    uint4 part[16 * 8 * 9 * 2 * 4 * 128];
    uint4 gate[N_MAIN * 5 * 2 * 256];
    uint4 flag[16 * 8 * 32];
    uint4 qoff[16 * 4 * 2048];
    uint32_t flag_q[16];
    uint4 rare[N_MAIN * 17 * 256];
    float y[N_MOE * CAP * DM];
    uint2 routed[CAP * DM / 4];
    uint2 stat[SEQ];
    float r[SEQ];
    int idx[CAP];
    uint32_t flag_r[N_MOE], flag_y[N_MOE], flag_u[N_MOE];
    uint32_t epoch[N_MAIN + N_MOE];
};
__device__ Scratch g_scratch;

__device__ __forceinline__ uint32_t smem_u32(const void* p) { return (uint32_t)__cvta_generic_to_shared(p); }
__device__ __forceinline__ void mbar_init(uint32_t bar, uint32_t cnt) {
    asm volatile("mbarrier.init.shared::cta.b64 [%0], %1;" ::"r"(bar), "r"(cnt) : "memory");
}
__device__ __forceinline__ void mbar_wait(uint32_t bar, uint32_t parity) {
    asm volatile(
        "{\n.reg .pred p;\n"
        "LOOP:\n"
        "mbarrier.try_wait.parity.shared::cta.b64 p, [%0], %1;\n"
        "@!p bra.uni LOOP;\n"
        "DONE:\n}\n" ::"r"(bar), "r"(parity) : "memory");
}
__device__ __forceinline__ void mbar_wait_hot(uint32_t bar, uint32_t parity) {
    asm volatile(
        "{\n.reg .pred p;\n.reg .u32 c;\n"
        "mbarrier.test_wait.parity.shared::cta.b64 p, [%0], %1;\n"
        "@p bra.uni DONE;\n"
        "mov.u32 c, 0;\n"
        "LOOP:\n"
        "mbarrier.try_wait.parity.shared::cta.b64 p, [%0], %1;\n"
        "@p bra.uni DONE;\n"
        "add.u32 c, c, 1;\n"
        "setp.lt.u32 p, c, 2000000;\n"
        "@p bra.uni LOOP;\n"
        "trap;\n"
        "DONE:\n}\n" ::"r"(bar), "r"(parity) : "memory");
}
__device__ __forceinline__ void mbar_wait_bounded(uint32_t bar, uint32_t parity) {
    asm volatile(
        "{\n.reg .pred p;\n.reg .u32 c;\n"
        "mov.u32 c, 0;\n"
        "LOOP:\n"
        "mbarrier.try_wait.parity.shared::cta.b64 p, [%0], %1;\n"
        "@p bra.uni DONE;\n"
        "add.u32 c, c, 1;\n"
        "setp.lt.u32 p, c, 2000000;\n"
        "@p bra.uni LOOP;\n"
        "trap;\n"
        "DONE:\n}\n" ::"r"(bar), "r"(parity) : "memory");
}
__device__ __forceinline__ void mbar_wait_sleep(uint32_t bar, uint32_t parity) {
    asm volatile(
        "{\n.reg .pred p;\n.reg .u32 c;\n"
        "mov.u32 c, 0;\n"
        "LOOP:\n"
        "mbarrier.test_wait.parity.shared::cta.b64 p, [%0], %1;\n"
        "@p bra.uni DONE;\n"
        "nanosleep.u32 500;\n"
        "add.u32 c, c, 1;\n"
        "setp.lt.u32 p, c, 1000000;\n"
        "@p bra.uni LOOP;\n"
        "trap;\n"
        "DONE:\n}\n" ::"r"(bar), "r"(parity) : "memory");
}
__device__ __forceinline__ void mbar_expect_tx(uint32_t bar, uint32_t bytes) {
    asm volatile("mbarrier.arrive.expect_tx.shared::cta.b64 _, [%0], %1;" ::"r"(bar), "r"(bytes) : "memory");
}
template <int OFF>
__device__ __forceinline__ void release_at(uint32_t bar) {
    asm volatile(
        "{\n.reg .pred p;\n"
        "setp.ne.u32 p, %0, 0;\n"
        "@p mbarrier.arrive.shared::cluster.b64 _, [%0 + %1];\n}\n" ::"r"(bar), "n"(OFF) : "memory");
}
__device__ __forceinline__ void sched_fence(int zero) {
    asm volatile("{\n.reg .pred p;\n.reg .u32 c;\nsetp.ne.s32 p, %0, 0;\n@p mov.u32 c, %%clock;\n@p st.shared.u32 [%0], c;\n}\n" ::"r"(zero) : "memory");
}
__device__ __forceinline__ bool elect_one() {
    uint32_t r;
    asm volatile("{\n.reg .pred p;\nelect.sync _|p, 0xffffffff;\nselp.u32 %0, 1, 0, p;\n}\n" : "=r"(r));
    return r;
}
__device__ __forceinline__ uint32_t opaque(uint32_t v) {
    uint32_t r;
    asm volatile("mov.u32 %0, %1;" : "=r"(r) : "r"(v));
    return r;
}
__device__ __forceinline__ void tma_2d(uint32_t dst, const CUtensorMap* tm, uint32_t bar, int c0, int c1) {
    asm volatile(
        "cp.async.bulk.tensor.2d.shared::cluster.global.mbarrier::complete_tx::bytes [%0], [%1, {%3, %4}], [%2];"
        ::"r"(dst), "l"(tm), "r"(bar), "r"(c0), "r"(c1) : "memory");
}
__device__ __forceinline__ void tma_3d(uint32_t dst, const CUtensorMap* tm, uint32_t bar, int c0, int c1, int c2) {
    asm volatile(
        "cp.async.bulk.tensor.3d.shared::cluster.global.mbarrier::complete_tx::bytes [%0], [%1, {%3, %4, %5}], [%2];"
        ::"r"(dst), "l"(tm), "r"(bar), "r"(c0), "r"(c1), "r"(c2) : "memory");
}
__device__ __forceinline__ void tma_2d_mc(uint32_t dst, const CUtensorMap* tm, uint32_t bar, int c0, int c1) {
    asm volatile(
        "cp.async.bulk.tensor.2d.shared::cluster.global.mbarrier::complete_tx::bytes.multicast::cluster "
        "[%0], [%1, {%3, %4}], [%2], %5;"
        ::"r"(dst), "l"(tm), "r"(bar), "r"(c0), "r"(c1), "h"((uint16_t)3) : "memory");
}
__device__ __forceinline__ void tma_prefetch(const CUtensorMap* tm, int c0, int c1) {
    asm volatile("cp.async.bulk.prefetch.tensor.2d.L2.global [%0, {%1, %2}];" ::"l"(tm), "r"(c0), "r"(c1) : "memory");
}
__device__ __forceinline__ void mbar_arrive(uint32_t bar) {
    asm volatile("mbarrier.arrive.shared::cta.b64 _, [%0];" ::"r"(bar) : "memory");
}
__device__ __forceinline__ void flag_set(uint32_t* f, uint32_t v) {
    asm volatile("st.release.gpu.global.u32 [%0], %1;" ::"l"(f), "r"(v) : "memory");
}
template <int SLEEP_NS = 0>
__device__ __forceinline__ void flag_wait(const uint32_t* f, uint32_t v) {
    asm volatile(
        "{\n.reg .pred p;\n.reg .u32 c;\n"
        "LOOP:\n"
        "setp.ne.u32 p, %2, 0;\n"
        "@p nanosleep.u32 %2;\n"
        "ld.acquire.gpu.global.u32 c, [%0];\n"
        "setp.ne.u32 p, c, %1;\n"
        "@p bra LOOP;\n}\n" ::"l"(f), "r"(v), "n"(SLEEP_NS) : "memory");
}
template <int SLEEP_NS>
__device__ __forceinline__ void flag_wait_bounded(const uint32_t* f, uint32_t v) {
    asm volatile(
        "{\n.reg .pred p;\n.reg .u32 c, n;\n"
        "mov.u32 n, 0;\n"
        "LOOP:\n"
        "setp.ne.u32 p, %2, 0;\n"
        "@p nanosleep.u32 %2;\n"
        "ld.acquire.gpu.global.u32 c, [%0];\n"
        "setp.eq.u32 p, c, %1;\n"
        "@p bra DONE;\n"
        "add.u32 n, n, 1;\n"
        "setp.lt.u32 p, n, %3;\n"
        "@p bra LOOP;\n"
        "trap;\n"
        "DONE:\n}\n" ::"l"(f), "r"(v), "n"(SLEEP_NS), "n"(2000000) : "memory");
}
__device__ __forceinline__ void hmma(float (&d)[4], uint32_t a0, uint32_t a1, uint32_t a2, uint32_t a3, uint32_t b0, uint32_t b1) {
    asm volatile("mma.sync.aligned.m16n8k16.row.col.f32.bf16.bf16.f32 {%0,%1,%2,%3}, {%4,%5,%6,%7}, {%8,%9}, {%0,%1,%2,%3};"
                 : "+f"(d[0]), "+f"(d[1]), "+f"(d[2]), "+f"(d[3]) : "r"(a0), "r"(a1), "r"(a2), "r"(a3), "r"(b0), "r"(b1));
}
__device__ __forceinline__ void hmma8(float (&d)[4], uint32_t a0, uint32_t a1, uint32_t b0) {
    asm volatile("mma.sync.aligned.m16n8k8.row.col.f32.bf16.bf16.f32 {%0,%1,%2,%3}, {%4,%5}, {%6}, {%0,%1,%2,%3};"
                 : "+f"(d[0]), "+f"(d[1]), "+f"(d[2]), "+f"(d[3]) : "r"(a0), "r"(a1), "r"(b0));
}
__device__ __forceinline__ void ldsm4(uint32_t addr, uint32_t& a, uint32_t& b, uint32_t& c, uint32_t& d) {
    asm volatile("ldmatrix.sync.aligned.m8n8.x4.shared.b16 {%0, %1, %2, %3}, [%4];"
                 : "=r"(a), "=r"(b), "=r"(c), "=r"(d) : "r"(addr) : "memory");
}
__device__ __forceinline__ void stsm4(uint32_t addr, uint32_t a, uint32_t b, uint32_t c, uint32_t d) {
    asm volatile("stmatrix.sync.aligned.m8n8.x4.shared.b16 [%4], {%0, %1, %2, %3};"
                 ::"r"(a), "r"(b), "r"(c), "r"(d), "r"(addr) : "memory");
}
__device__ __forceinline__ uint32_t bf2_sub(uint32_t a, uint32_t b) {
    uint32_t d;
    asm("sub.rn.bf16x2 %0, %1, %2;" : "=r"(d) : "r"(a), "r"(b));
    return d;
}
template <int LUT>
__device__ __forceinline__ uint32_t lop3(uint32_t a, uint32_t b, uint32_t c) {
    uint32_t d;
    asm("lop3.b32 %0, %1, %2, %3, %4;" : "=r"(d) : "r"(a), "r"(b), "r"(c), "n"(LUT));
    return d;
}
__device__ __forceinline__ float rcp(float x) {
    float y;
    asm("rcp.approx.ftz.f32 %0, %1;" : "=f"(y) : "f"(x));
    return y;
}
__device__ __forceinline__ void bar_sync(int id) { asm volatile("bar.sync %0, 256;" ::"r"(id) : "memory"); }
__device__ __forceinline__ void bar_arrive(int id) { asm volatile("bar.arrive %0, 256;" ::"r"(id) : "memory"); }
__device__ __forceinline__ void wg_fence() { asm volatile("wgmma.fence.sync.aligned;" ::: "memory"); }
__device__ __forceinline__ void wg_commit() { asm volatile("wgmma.commit_group.sync.aligned;" ::: "memory"); }
template <int N> __device__ __forceinline__ void wg_wait() { asm volatile("wgmma.wait_group.sync.aligned %0;" ::"n"(N) : "memory"); }
template <int N>
__device__ __forceinline__ void pin(float (&d)[N]) {
#pragma unroll
    for (int i = 0; i < N; i++) asm volatile("" : "+f"(d[i])::"memory");
}
__device__ __forceinline__ uint32_t pack_bf16(float lo, float hi) {
    uint32_t r;
    asm("cvt.rn.bf16x2.f32 %0, %1, %2;" : "=r"(r) : "f"(hi), "f"(lo));
    return r;
}
__device__ __forceinline__ float bf_lo(uint32_t v) { return __uint_as_float(v << 16); }
__device__ __forceinline__ float bf_hi(uint32_t v) { return __uint_as_float(v & 0xffff0000u); }
__device__ __forceinline__ float bf_round(float v) { return __bfloat162float(__float2bfloat16_rn(v)); }
__device__ __forceinline__ float ex2(float x) {
    float y;
    asm("ex2.approx.ftz.f32 %0, %1;" : "=f"(y) : "f"(x));
    return y;
}
__device__ __forceinline__ void sts128(uint32_t addr, uint32_t a, uint32_t b, uint32_t c, uint32_t d) {
    asm volatile("st.shared.v4.b32 [%0], {%1, %2, %3, %4};" ::"r"(addr), "r"(a), "r"(b), "r"(c), "r"(d) : "memory");
}
__device__ __forceinline__ void lds128(uint32_t addr, uint32_t& a, uint32_t& b, uint32_t& c, uint32_t& d) {
    asm volatile("ld.shared.v4.b32 {%0, %1, %2, %3}, [%4];" : "=r"(a), "=r"(b), "=r"(c), "=r"(d) : "r"(addr) : "memory");
}

template <int OFF>
__device__ __forceinline__ void lds128_if(bool on, uint32_t addr, uint32_t& a, uint32_t& b, uint32_t& c, uint32_t& d) {
    asm volatile("{\n.reg .pred p;\nsetp.ne.u32 p, %5, 0;\n@p ld.shared.v4.b32 {%0, %1, %2, %3}, [%4 + %6];\n}\n"
                 : "+r"(a), "+r"(b), "+r"(c), "+r"(d) : "r"(addr), "r"((uint32_t)on), "n"(OFF) : "memory");
}

template <int TB>
__device__ __forceinline__ void wgmma_rs(float (&d)[64], uint32_t a0, uint32_t a1, uint32_t a2, uint32_t a3,
                                         uint64_t desc, int scale_d) {
    asm volatile(
        "{\n.reg .pred p;\nsetp.ne.b32 p, %69, 0;\n"
        "wgmma.mma_async.sync.aligned.m64n128k16.f32.bf16.bf16 "
        "{%0,%1,%2,%3,%4,%5,%6,%7,%8,%9,%10,%11,%12,%13,%14,%15,%16,%17,%18,%19,%20,%21,%22,%23,%24,%25,%26,%27,%28,%29,%30,%31,"
        "%32,%33,%34,%35,%36,%37,%38,%39,%40,%41,%42,%43,%44,%45,%46,%47,%48,%49,%50,%51,%52,%53,%54,%55,%56,%57,%58,%59,%60,%61,%62,%63},"
        "{%64,%65,%66,%67}, %68, p, 1, 1, %70;\n}\n"
        : "+f"(d[0]), "+f"(d[1]), "+f"(d[2]), "+f"(d[3]), "+f"(d[4]), "+f"(d[5]), "+f"(d[6]), "+f"(d[7]),
          "+f"(d[8]), "+f"(d[9]), "+f"(d[10]), "+f"(d[11]), "+f"(d[12]), "+f"(d[13]), "+f"(d[14]), "+f"(d[15]),
          "+f"(d[16]), "+f"(d[17]), "+f"(d[18]), "+f"(d[19]), "+f"(d[20]), "+f"(d[21]), "+f"(d[22]), "+f"(d[23]),
          "+f"(d[24]), "+f"(d[25]), "+f"(d[26]), "+f"(d[27]), "+f"(d[28]), "+f"(d[29]), "+f"(d[30]), "+f"(d[31]),
          "+f"(d[32]), "+f"(d[33]), "+f"(d[34]), "+f"(d[35]), "+f"(d[36]), "+f"(d[37]), "+f"(d[38]), "+f"(d[39]),
          "+f"(d[40]), "+f"(d[41]), "+f"(d[42]), "+f"(d[43]), "+f"(d[44]), "+f"(d[45]), "+f"(d[46]), "+f"(d[47]),
          "+f"(d[48]), "+f"(d[49]), "+f"(d[50]), "+f"(d[51]), "+f"(d[52]), "+f"(d[53]), "+f"(d[54]), "+f"(d[55]),
          "+f"(d[56]), "+f"(d[57]), "+f"(d[58]), "+f"(d[59]), "+f"(d[60]), "+f"(d[61]), "+f"(d[62]), "+f"(d[63])
        : "r"(a0), "r"(a1), "r"(a2), "r"(a3), "l"(desc), "r"(scale_d), "n"(TB));
}
__device__ __forceinline__ void wgmma_ss(float (&d)[64], uint64_t desc_a, uint64_t desc_b, int scale_d) {
    asm volatile(
        "{\n.reg .pred p;\nsetp.ne.b32 p, %66, 0;\n"
        "wgmma.mma_async.sync.aligned.m64n128k16.f32.bf16.bf16 "
        "{%0,%1,%2,%3,%4,%5,%6,%7,%8,%9,%10,%11,%12,%13,%14,%15,%16,%17,%18,%19,%20,%21,%22,%23,%24,%25,%26,%27,%28,%29,%30,%31,"
        "%32,%33,%34,%35,%36,%37,%38,%39,%40,%41,%42,%43,%44,%45,%46,%47,%48,%49,%50,%51,%52,%53,%54,%55,%56,%57,%58,%59,%60,%61,%62,%63},"
        "%64, %65, p, 1, 1, 0, 1;\n}\n"
        : "+f"(d[0]), "+f"(d[1]), "+f"(d[2]), "+f"(d[3]), "+f"(d[4]), "+f"(d[5]), "+f"(d[6]), "+f"(d[7]),
          "+f"(d[8]), "+f"(d[9]), "+f"(d[10]), "+f"(d[11]), "+f"(d[12]), "+f"(d[13]), "+f"(d[14]), "+f"(d[15]),
          "+f"(d[16]), "+f"(d[17]), "+f"(d[18]), "+f"(d[19]), "+f"(d[20]), "+f"(d[21]), "+f"(d[22]), "+f"(d[23]),
          "+f"(d[24]), "+f"(d[25]), "+f"(d[26]), "+f"(d[27]), "+f"(d[28]), "+f"(d[29]), "+f"(d[30]), "+f"(d[31]),
          "+f"(d[32]), "+f"(d[33]), "+f"(d[34]), "+f"(d[35]), "+f"(d[36]), "+f"(d[37]), "+f"(d[38]), "+f"(d[39]),
          "+f"(d[40]), "+f"(d[41]), "+f"(d[42]), "+f"(d[43]), "+f"(d[44]), "+f"(d[45]), "+f"(d[46]), "+f"(d[47]),
          "+f"(d[48]), "+f"(d[49]), "+f"(d[50]), "+f"(d[51]), "+f"(d[52]), "+f"(d[53]), "+f"(d[54]), "+f"(d[55]),
          "+f"(d[56]), "+f"(d[57]), "+f"(d[58]), "+f"(d[59]), "+f"(d[60]), "+f"(d[61]), "+f"(d[62]), "+f"(d[63])
        : "l"(desc_a), "l"(desc_b), "r"(scale_d));
}
__device__ __forceinline__ void wgmma_rs64(float (&d)[32], uint32_t a0, uint32_t a1, uint32_t a2, uint32_t a3,
                                           uint64_t desc, int scale_d) {
    asm volatile(
        "{\n.reg .pred p;\nsetp.ne.b32 p, %37, 0;\n"
        "wgmma.mma_async.sync.aligned.m64n64k16.f32.bf16.bf16 "
        "{%0,%1,%2,%3,%4,%5,%6,%7,%8,%9,%10,%11,%12,%13,%14,%15,%16,%17,%18,%19,%20,%21,%22,%23,%24,%25,%26,%27,%28,%29,%30,%31},"
        "{%32,%33,%34,%35}, %36, p, 1, 1, 1;\n}\n"
        : "+f"(d[0]), "+f"(d[1]), "+f"(d[2]), "+f"(d[3]), "+f"(d[4]), "+f"(d[5]), "+f"(d[6]), "+f"(d[7]),
          "+f"(d[8]), "+f"(d[9]), "+f"(d[10]), "+f"(d[11]), "+f"(d[12]), "+f"(d[13]), "+f"(d[14]), "+f"(d[15]),
          "+f"(d[16]), "+f"(d[17]), "+f"(d[18]), "+f"(d[19]), "+f"(d[20]), "+f"(d[21]), "+f"(d[22]), "+f"(d[23]),
          "+f"(d[24]), "+f"(d[25]), "+f"(d[26]), "+f"(d[27]), "+f"(d[28]), "+f"(d[29]), "+f"(d[30]), "+f"(d[31])
        : "r"(a0), "r"(a1), "r"(a2), "r"(a3), "l"(desc), "r"(scale_d));
}
__device__ __forceinline__ void wgmma_ss64(float (&d)[32], uint64_t desc_a, uint64_t desc_b, int scale_d) {
    asm volatile(
        "{\n.reg .pred p;\nsetp.ne.b32 p, %34, 0;\n"
        "wgmma.mma_async.sync.aligned.m64n64k16.f32.bf16.bf16 "
        "{%0,%1,%2,%3,%4,%5,%6,%7,%8,%9,%10,%11,%12,%13,%14,%15,%16,%17,%18,%19,%20,%21,%22,%23,%24,%25,%26,%27,%28,%29,%30,%31},"
        "%32, %33, p, 1, 1, 0, 1;\n}\n"
        : "+f"(d[0]), "+f"(d[1]), "+f"(d[2]), "+f"(d[3]), "+f"(d[4]), "+f"(d[5]), "+f"(d[6]), "+f"(d[7]),
          "+f"(d[8]), "+f"(d[9]), "+f"(d[10]), "+f"(d[11]), "+f"(d[12]), "+f"(d[13]), "+f"(d[14]), "+f"(d[15]),
          "+f"(d[16]), "+f"(d[17]), "+f"(d[18]), "+f"(d[19]), "+f"(d[20]), "+f"(d[21]), "+f"(d[22]), "+f"(d[23]),
          "+f"(d[24]), "+f"(d[25]), "+f"(d[26]), "+f"(d[27]), "+f"(d[28]), "+f"(d[29]), "+f"(d[30]), "+f"(d[31])
        : "l"(desc_a), "l"(desc_b), "r"(scale_d));
}
__device__ __forceinline__ uint64_t desc_kmajor(uint32_t tile16, int ks) {
    uint32_t lo = tile16 + ((ks >> 2) * 1024 + (ks & 3) * 2 + (1u << 16));
    return ((uint64_t)0x40000040u << 32) | lo;
}
__device__ __forceinline__ uint64_t desc_nmajor(uint32_t tile16, int ks) {
    uint32_t lo = tile16 + (ks * 128 + (1024u << 16));
    return ((uint64_t)0x40000040u << 32) | lo;
}
template <int TB>
__device__ __forceinline__ void mma_tile(float (&d)[64], const uint32_t* a, uint32_t tile16, int accumulate) {
#pragma unroll
    for (int ks = 0; ks < 8; ks++)
        wgmma_rs<TB>(d, a[4 * ks], a[4 * ks + 1], a[4 * ks + 2], a[4 * ks + 3],
                     TB ? desc_nmajor(tile16, ks) : desc_kmajor(tile16, ks), ks == 0 ? accumulate : 1);
    wg_commit();
}

template <int V> struct cint { static constexpr int value = V; };
#define GPF 126
#define XN 2
#define FINK 3
#define G4 0
#define QAT 110
#define FSPLIT 2
#define SPLIT 32
#define SPLITO 24

#define TRM(i)
#define TR(i)
#define TG(i)
#define PT(k)
#define TS(k)
#define TA(k)
#define TL(k)
#define TF(i)
#define TH(w, i)
#define TC(k)

__device__ __forceinline__ float silu_f(float v) { return v * rcp(1.f + ex2(v * -1.4426950408889634f)); }

__device__ __forceinline__ float inv_den(float var) {
    float r;
    asm("sqrt.approx.f32 %0, %1;" : "=f"(r) : "f"(bf_round(bf_round(var) + 1e-5f)));
    return rcp(bf_round(r));
}
__device__ __forceinline__ uint32_t normalise(uint32_t x2, uint32_t mm, float id) {
    const uint32_t d = bf2_sub(x2, mm);
    return pack_bf16(bf_lo(d) * id, bf_hi(d) * id);
}

__device__ __forceinline__ uint32_t silu2(uint32_t u) { return pack_bf16(silu_f(bf_lo(u)), silu_f(bf_hi(u))); }

__device__ __forceinline__ uint32_t silu2_ln(uint32_t u) {
    const float a = bf_lo(u), b = bf_hi(u);
    const float da = 1.f + ex2(a * -1.4426950408889634f), db = 1.f + ex2(b * -1.4426950408889634f);
    const float r = rcp(da * db);
    return pack_bf16(a * db * r, b * da * r);
}

__device__ __forceinline__ uint2 load_stat(Scratch* sc, int row) {
    uint2 v;
    asm volatile("ld.relaxed.gpu.global.v2.u32 {%0, %1}, [%2];" : "=r"(v.x), "=r"(v.y) : "l"(sc->stat + row) : "memory");
    return make_uint2(__byte_perm(v.x, 0, 0x1010), v.y);
}

constexpr int FSLOT = 6;
__device__ __forceinline__ void ffn_role(Scratch* sc, uint32_t ring, uint32_t ffull, uint32_t fempty, uint32_t alldone, int e, uint32_t ep, int warp,
                                         const __nv_bfloat16* __restrict__ x) {
    const uint32_t xs = ring + FSLOT * TILE_BYTES, hs = xs + 10 * 1024, cand = hs + 8 * 1024, sig = cand + 256;
    int tid;
    asm volatile("mov.u32 %0, %%tid.x;" : "=r"(tid));
    const int lane = tid & 31;
    [[maybe_unused]] const int wg = warp >> 2;
    const int nb = e == N_MOE - 1 ? 6 : 7, nkt = (nb + 1) >> 1;
    auto sync = [] { asm volatile("bar.sync 3, 256;" ::: "memory"); };
    if (tid < N_MOE) flag_wait(sc->flag_r + tid, ep);
    sync();
    TR(6);

    {
        uint32_t key[8];
#pragma unroll
        for (int i = 0; i < 8; i++) {
            const int j = warp * 256 + i * 32 + lane;
            const uint32_t u = __float_as_uint(__ldcg(sc->r + j) + 0.f);
            key[i] = (((u & 0x80000000u) ? ~u : (u | 0x80000000u)) & 0xffff0000u) | (uint32_t)(SEQ - j);
        }
#pragma unroll 1
        for (int k = 0; k < CAP; k++) {
            uint32_t b = key[0];
#pragma unroll
            for (int i = 1; i < 8; i++) b = max(b, key[i]);
            b = __reduce_max_sync(0xffffffffu, b);
#pragma unroll
            for (int i = 0; i < 8; i++) if (key[i] == b) key[i] = 0;
            if (lane == 0) asm volatile("st.shared.u32 [%0], %1;" ::"r"(cand + (warp * 8 + k) * 4), "r"(b) : "memory");
        }
    }
    sync();
    {
        uint32_t k0, k1, b = 0;
        asm volatile("ld.shared.v2.u32 {%0, %1}, [%2];" : "=r"(k0), "=r"(k1) : "r"(cand + lane * 8));
#pragma unroll 1
        for (int k = 0; k <= warp; k++) {
            b = __reduce_max_sync(0xffffffffu, max(k0, k1));
            if (k0 == b) k0 = 0;
            if (k1 == b) k1 = 0;
        }
        const int row = SEQ - (int)(b & 0xffffu);
        const uint2 st = load_stat(sc, row);
        uint4 v[3];
#pragma unroll
        for (int k = 0; k < 3; k++) v[k] = __ldg((const uint4*)(x + (size_t)row * DM) + min(lane + 32 * k, DM / 8 - 1));
#pragma unroll
        for (int k = 0; k < 3; k++) {
            const int i = lane + 32 * k;
            const float id = __uint_as_float(st.y);
            if (i < DM / 8)
                sts128(xs + (i >> 3) * 1024 + warp * 128 + (((i & 7) ^ warp) << 4), normalise(v[k].x, st.x, id), normalise(v[k].y, st.x, id),
                       normalise(v[k].z, st.x, id), normalise(v[k].w, st.x, id));
        }
        asm volatile("fence.proxy.async.shared::cta;" ::: "memory");
        if (lane == 0) {
            const float sg = bf_round(rcp(1.f + __expf(-__ldcg(sc->r + row))));
            asm volatile("st.shared.v2.b32 [%0], {%1, %2};" ::"r"(sig + warp * 8), "f"(sg), "r"(row) : "memory");
        }
    }
    sync();
    TR(7);

    {
        float acc[64];
        const int g = lane >> 2, t4 = lane & 3;
        auto block = [&](uint32_t a, uint32_t n, int step, int halves) {
#pragma unroll 1
            for (int i = 0; i < halves; i += 2, n += step) {
                const uint32_t s = n % FSLOT;
                mbar_wait(ffull + 8 * s, (n / FSLOT) & 1);
                const uint32_t a16 = (((a + i * 1024) & 0x3FFFFu) >> 4) | (1u << 16);
                const uint32_t b16 = ((ring + s * TILE_BYTES) & 0x3FFFFu) >> 4;
                auto mmas = [&](auto n_c) {
                    wg_fence();
#pragma unroll
                    for (int ks = 0; ks < decltype(n_c)::value; ks++)
                        wgmma_ss(acc, ((uint64_t)0x40000000u << 32) | (a16 + (ks >> 2) * 64 + (ks & 3) * 2), desc_nmajor(b16, ks), ks || i);
                    wg_commit();
                    wg_wait<0>();
                };
                if (i + 1 < halves) mmas(cint<8>());
                else mmas(cint<4>());
                if (lane == 0) mbar_arrive(fempty + 8 * s);
            }
            pin(acc);
        };
#pragma unroll 1
        for (int o = warp >> 2; o < nb; o += 2) {
            const bool pair = (o | 1) < nb;
            block(xs, 5 * (o & ~1) + (pair ? o & 1 : 0), pair ? 2 : 1, 10);
#pragma unroll
            for (int j = 0; j < 8; j++) {
                uint32_t h = pack_bf16(silu_f(bf_round(acc[4 * j])), silu_f(bf_round(acc[4 * j + 1])));
                asm("mul.rn.bf16x2 %0, %0, %1;" : "+r"(h) : "r"(pack_bf16(acc[32 + 4 * j], acc[33 + 4 * j])));
                asm volatile("st.shared.u32 [%0], %1;" ::"r"(hs + o * 1024 + g * 128 + ((j ^ g) << 4) + t4 * 4), "r"(h) : "memory");
            }
        }
        asm volatile("fence.proxy.async.shared::cta;" ::: "memory");
        sync();
        TR(8);
#pragma unroll 1
        for (int o = warp >> 2; o < 5; o += 2) {
            block(hs, 5 * nb + (o & ~1) * nkt + (o & 1), o < 4 ? 2 : 1, nb);
            if ((warp & 3) == 0) {
#pragma unroll
                for (int j = 0; j < 16; j++)
                    *(float2*)(sc->y + (e * CAP + g) * DM + o * 128 + j * 8 + t4 * 2) = make_float2(acc[4 * j], acc[4 * j + 1]);
            }
        }
    }
    sync();
    TR(9);
    if (tid == 0) flag_set(sc->flag_y + e, ep);
    if (tid < N_MOE) flag_wait(sc->flag_y + tid, ep);
    sync();
    if (lane == 0) mbar_arrive(alldone);
#pragma unroll 1
    for (int t = tid; t < 320; t += 256) {
        const int i = 2 * e * DM + t * 4;
        float4 y = __ldcg((const float4*)(sc->y + i));
#pragma unroll
        for (int j = 1; j < N_MOE; j++) {
            const float4 z = __ldcg((const float4*)(sc->y + j * CAP * DM + i));
            y.x += z.x; y.y += z.y; y.z += z.z; y.w += z.w;
        }
        float sg;
        int row;
        asm volatile("ld.shared.v2.b32 {%0, %1}, [%2];" : "=f"(sg), "=r"(row) : "r"(sig + (i / DM) * 8));
        const int o4 = (row * DM + i % DM) / 4;
        const uint2 v = __ldg((const uint2*)x + o4), st = load_stat(sc, row);
        uint32_t u0 = normalise(v.x, st.x, __uint_as_float(st.y)), u1 = normalise(v.y, st.x, __uint_as_float(st.y));
        asm("add.rn.bf16x2 %0, %0, %1;" : "+r"(u0) : "r"(pack_bf16(bf_round(y.x) * sg, bf_round(y.y) * sg)));
        asm("add.rn.bf16x2 %0, %0, %1;" : "+r"(u1) : "r"(pack_bf16(bf_round(y.z) * sg, bf_round(y.w) * sg)));
        sc->routed[i / 4] = make_uint2(silu2(u0), silu2(u1));
        if (i % DM == 0) sc->idx[i / DM] = row;
    }
    sync();
    TR(10);
    if (tid == 0) flag_set(sc->flag_u + e, ep);
}

__global__ void __launch_bounds__(384, 1)
fused_attn_kernel(const __nv_bfloat16* __restrict__ x, const __nv_bfloat16* __restrict__ wr,
                  __nv_bfloat16* __restrict__ out, Scratch* sc,
                  const __grid_constant__ CUtensorMap tm_x, const __grid_constant__ CUtensorMap tm_wq,
                  const __grid_constant__ CUtensorMap tm_k, const __grid_constant__ CUtensorMap tm_v,
                  const __grid_constant__ CUtensorMap tm_wo, const __grid_constant__ CUtensorMap tm_g,
                  const __grid_constant__ CUtensorMap tm_u, const __grid_constant__ CUtensorMap tm_d) {
    PT(0);
    extern __shared__ __align__(16) uint8_t smem_raw[];
    const uint32_t ring = smem_u32(smem_raw);
    const uint32_t stash = ring + NSLOT * TILE_BYTES;
    const uint32_t bars = stash + 3 * TILE_BYTES;
    const uint32_t full = bars, empty = bars + 32;
    const uint32_t xfull = bars + 64;
    const uint32_t rfull = bars + 144;
    const uint32_t rdone = bars + 288;
    const uint32_t vacant = bars + 336, routed = bars + 344, xgfull = bars + 352, gated = bars + 360;
    const uint32_t soon = bars + 376, qfull = bars + 384, epv = bars + 392, alldone = bars + 400;
    const uint32_t epoch = bars + 368;
    [[maybe_unused]] const uint32_t trbuf = bars + 416;
    const uint32_t ffull = rfull, fempty = rfull + 8 * FSLOT, qdone = rdone, h1done = rdone + 32, wperm = trbuf;

    const int warp = __shfl_sync(0xffffffffu, threadIdx.x >> 5, 0), wg = warp >> 2;
    const int rank = blockIdx.x & 1;
    const int cl = blockIdx.x >> 1;
    const int r7 = ((cl - 36) * 37) >> 8;
    const int qp = cl < 36 ? (cl < 4 ? 0 : (cl - 4) & 7) : cl - 35 - 7 * r7;
    const int grp = cl < 4 ? cl + 4 : cl < 36 ? (cl - 4) >> 3 : r7 + 4;
    const bool helper = blockIdx.x >= N_MAIN;
    const int qt = helper ? (blockIdx.x - N_MAIN) * 4 : qp * 2 + rank;

    auto load_x = [&](int w, int i, int tile) {
        const uint32_t bar = xfull + (w * 5 + i) * 8;
        mbar_expect_tx(bar, 16384);
        tma_3d(ring + (i == 4 ? 2 : 3 + i) * TILE_BYTES + w * 16384, &tm_x, bar, 0, tile * 128 + w * 64, i == 0 ? 8 : 2 * i - 2);
    };
    if (warp == 4) {
        if (elect_one()) {
#pragma unroll
            for (int i = 0; i < 10; i++) mbar_init(xfull + 8 * i, 1);
#pragma unroll
            for (int i = 0; i < XN; i++) load_x(i & 1, i >> 1, qt);
            asm volatile("fence.mbarrier_init.release.cluster;" ::: "memory");
        }
        __syncwarp();
    }
    PT(6);
    if ((ring & 0xFFFFFFu) != RING_OFFSET) return;
    PT(7);
    if (warp >= 5 && elect_one()) {
        if (warp == 5) {
#pragma unroll
            for (int i = 0; i < NSLOT; i++) { mbar_init(full + 8 * i, 1); mbar_init(empty + 8 * i, 16); }
            mbar_arrive(full + 16);
            mbar_arrive(full + 24);
        } else if (warp == 6) {
#pragma unroll
            for (int i = 0; i < 6; i++) mbar_init(rdone + 8 * i, helper ? 8 : 4);
        } else if (warp == 7) {
            mbar_init(vacant, 8); mbar_init(routed, 32); mbar_init(xgfull, 1); mbar_init(gated, 8); mbar_init(soon, 1);
            mbar_init(qfull, 1); mbar_init(epv, 1); mbar_init(alldone, 8);
        } else if (warp == 8) {
            asm volatile("prefetch.tensormap [%0];" ::"l"(&tm_wq) : "memory");
        } else {
#pragma unroll
            for (int i = 0; i < 6; i++) mbar_init(rfull + ((warp - 9) * 6 + i) * 8, helper && warp == 10 ? 4 : 1);
        }
        asm volatile("fence.mbarrier_init.release.cluster;" ::: "memory");
    }
    __syncwarp();
    PT(1);
    asm volatile("barrier.cluster.arrive.relaxed.aligned;" ::: "memory");
    if (warp == 4) {
        if (elect_one()) {
#pragma unroll
            for (int i = XN; i < 10; i++) load_x(i & 1, i >> 1, qt);
        }
        __syncwarp();
    }

    if (wg == 2) {
        asm volatile("setmaxnreg.dec.sync.aligned.u32 24;");
        asm volatile("barrier.cluster.wait.aligned;" ::: "memory");
        uint32_t lane;
        asm volatile("mov.u32 %0, %%laneid;" : "=r"(lane));
        PT(2);
        if (warp == 8 && helper) {
          if (elect_one()) {
#pragma unroll 1
            for (int t = 0; t < 4; t++) {
#pragma unroll 1
                for (int i = 0; i < 20; i++) {
                    const int s = i % 3;
                    mbar_wait(empty + 8 * s, ((t + (i + 1) / 3) & 1) ^ 1);
                    mbar_expect_tx(full + 8 * s, TILE_BYTES);
                    tma_2d_mc(ring + s * TILE_BYTES + rank * 16384, &tm_wq, full + 8 * s, (((i / 5) * 2 + rank) * 4 + 3) * 128 + 64,
                              ((i + 4) % 5) * 128);
                    if (t == 0 && i == 2) {
                        asm volatile("nanosleep.u32 1500;");
#pragma unroll 1
                        for (int k = 3 + ((blockIdx.x >> 1) & 1); k < 20; k += 2) tma_prefetch(&tm_wq, (((k / 5) * 2 + rank) * 4 + 3) * 128 + 64, ((k + 4) % 5) * 128);
                    }
                    if (i == 2 && t < 3) {
#pragma unroll 1
                        for (int k = 2; k < 8; k++) load_x(k & 1, k >> 1, qt + t + 1);
                    }
                    if (i == 18 && t < 3) {
                        mbar_wait(empty + 24, t & 1);
                        load_x(0, 0, qt + t + 1); load_x(1, 0, qt + t + 1);
                    }
                }
                if (t < 3) {
                    mbar_wait(empty + 16, t & 1);
                    mbar_arrive(full + 16);
                    load_x(0, 4, qt + t + 1); load_x(1, 4, qt + t + 1);
                }
            }
            const int e = blockIdx.x - N_MAIN, nb = e == N_MOE - 1 ? 6 : 7, nkt = (nb + 1) >> 1;
            mbar_wait(h1done, 0);
            uint32_t s = 0, ph = 1;
#pragma unroll 1
            for (int o0 = 0, w; o0 < nb + 5; o0 += w) {
                const bool up = o0 < nb;
                w = o0 + 1 < (up ? nb : nb + 5) ? 2 : 1;
#pragma unroll 1
                for (int k = 0; k < (up ? 5 : nkt) * w; k++) {
                    const int o = o0 + (k & (w - 1)), i = k >> (w - 1);
                    mbar_wait(fempty + 8 * s, ph);
                    mbar_expect_tx(ffull + 8 * s, TILE_BYTES);
                    const int c0 = up ? (e * 7 + o) * 64 : (o - nb) * 128, c1 = (up ? 0 : e * 448) + i * 128;
                    tma_2d(ring + s * TILE_BYTES, up ? &tm_g : &tm_d, ffull + 8 * s, c0, c1);
                    tma_2d(ring + s * TILE_BYTES + 16384, up ? &tm_u : &tm_d, ffull + 8 * s, up ? c0 : c0 + 64, c1);
                    if (++s == FSLOT) { s = 0; ph ^= 1; }
                }
            }
          }
        } else if (warp == 8) {
          if (elect_one()) {
            PT(3);
            auto coords = [&](int i, const CUtensorMap*& tm, int& c0, int& c1) {
                c0 = rank * 64;
                if (i < 20) {
                    const int ps = i / 5;
                    tm = &tm_wq; c1 = (i % 5 < 3 ? i % 5 : 7 - i % 5) * 128;
                    if (ps == 1) {
                        c0 = 0;
                        c1 = (i == 5 ? rank : i == 6 ? 2 : 4 - rank) * 128;
                    }
                    c0 += (grp * 4 + (ps < 2 ? 2 + ps : 3 - ps)) * 128;
                } else if (i < 148) {
                    const int u = i - 20;
                    const bool isk = (u == 0) || ((u & 1) && u != 127);
                    const int b = isk ? (u + 1) >> 1 : (u == 127 ? 63 : (u >> 1) - 1);
                    tm = isk ? &tm_k : &tm_v; c1 = (grp * 64 + b) * 128;
                } else {
                    tm = &tm_wo; c0 = (i < 152 ? ((i - 132) >> 1) ^ (grp >> 2) : (grp + ((i - 150) >> 1)) & 7) * 64; c1 = (grp * 4 + (i & 1) * 2 + rank) * 128;
                }
            };
#pragma unroll 1
            for (int i = 0; i < 168; i++) {
                const CUtensorMap* tm;
                int c0, c1;
                if (i == 8) i = 10;
                const int a = i < 8 ? i : i - 2;
                const int s = i < 20 ? a % 3 : (i & 3);
                const uint32_t ph = i < 20 ? ((a + 1) / 3) & 1 : ((i >> 2) & 1) ^ (s < 2);
                coords(i, tm, c0, c1);
                if (i == QAT) mbar_wait(qfull, 0);
                mbar_wait(empty + 8 * s, ph ^ 1);
                if (i == 6) {
                    mbar_expect_tx(full + 8 * s, TILE_BYTES / 2);
                    if (rank == 0) tma_2d_mc(ring + s * TILE_BYTES, tm, full + 8 * s, c0, c1);
                } else {
                    mbar_expect_tx(full + 8 * s, TILE_BYTES);
                    tma_2d_mc(ring + s * TILE_BYTES + rank * 16384, tm, full + 8 * s, c0, c1);
                }
                if (i == 140) mbar_arrive(soon);
                if (i >= 163 && i < 167) {
                    if (i == 163) {
                        TL(0);
                        mbar_wait(routed, 0);
                        asm volatile("fence.proxy.async.global;" ::: "memory");
                        TL(1);
                        mbar_expect_tx(xgfull, TILE_BYTES);
                    }
                    asm volatile("cp.async.bulk.shared::cluster.global.mbarrier::complete_tx::bytes [%0], [%1], 8192, [%2];"
                                 ::"r"(stash + 3 * 16384 + (i - 163) * 8192), "l"(sc->gate + blockIdx.x * 2560 + (i - 163) * 512), "r"(xgfull) : "memory");
                }
                if (i == 12) asm volatile("prefetch.tensormap [%0];\nprefetch.tensormap [%1];" ::"l"(&tm_k), "l"(&tm_v) : "memory");
                if (i == 140) asm volatile("prefetch.tensormap [%0];" ::"l"(&tm_wo) : "memory");
                if (i >= GPF && i < GPF + 10)
                    asm volatile("cp.async.bulk.prefetch.L2.global [%0], 4096;" ::"l"(sc->gate + blockIdx.x * 2560 + (i - GPF) * 256) : "memory");
                const int j = i < 2 ? 2 + i : i == 2 ? 4 + ((qp - 4) & 7) : i + 9;
                if (j < 168 && (j & 7) == qp && (j & ~1) != 8) {
                    coords(j, tm, c0, c1);
                    tma_prefetch(tm, c0, c1);
                }
            }
            sc->epoch[blockIdx.x] += 1;
          }
        } else if (warp == 9) {
            const uint32_t ep = sc->epoch[blockIdx.x] + 1;
            if (helper) {
#pragma unroll 1
                for (int t = 0; t < 4; t++) {
                    if (t == 3) {
                        mbar_wait_sleep(qdone + 40, 0);
                        if (lane == 0) flag_set(sc->flag_r + (blockIdx.x - N_MAIN), ep);
                    }
                    mbar_wait_sleep(qdone + 8 * t, 0);
                    if (lane == 0) flag_set(sc->flag_q + qt + t, ep);
                }
                if (lane == 0) sc->epoch[blockIdx.x] = ep;
            } else {
                mbar_wait_sleep(gated, 0);
                flag_wait_bounded<300>(sc->flag_q + qt, ep);
                asm volatile("fence.proxy.async.global;" ::: "memory");
                if (lane == 0) mbar_expect_tx(qfull, 16384);
                __syncwarp();
                if (lane < 8)
                    asm volatile("cp.async.bulk.shared::cluster.global.mbarrier::complete_tx::bytes [%0], [%1], 2048, [%2];"
                                 ::"r"(stash + 2 * TILE_BYTES + lane * 4096 + 2048),
                                   "l"(sc->qoff + ((qt * 4 + (grp >> 1)) * 8 + lane) * 256 + (grp & 1) * 128), "r"(qfull) : "memory");
            }
            mbar_wait_bounded(alldone, 0);
        } else if (helper) {
        } else if (warp == 10) {
            const uint32_t ep = sc->epoch[blockIdx.x] + 1;
            if (lane == 0) {
                asm volatile("st.shared.u32 [%0], %1;" ::"r"(epoch), "r"(ep) : "memory");
                mbar_arrive(epv);
            }
            mbar_wait_sleep(gated, 0);
            flag_wait<400>(sc->flag_u + (lane & 3), ep);
            __syncwarp();
            const int rrow = __ldcg(sc->idx + (lane & 7));
            uint32_t hit = __ballot_sync(0xffffffffu, lane < 8 && (rrow >> 7) == qt);
            while (hit) {
                const int k = __ffs(hit) - 1, row = __shfl_sync(0xffffffffu, rrow, k);
                hit &= hit - 1;
#pragma unroll 1
                for (int i = lane; i < 40; i += 32) {
                    const int th = ((row >> 4) & 7) * 32 + (row & 7) * 4 + (i & 3);
                    ((uint32_t*)sc->gate)[(((blockIdx.x * 5 + (i >> 3)) * 2 + 1) * 256 + th) * 4 + ((i >> 1) & 2) + ((row >> 3) & 1)] =
                        __ldcg((const uint32_t*)sc->routed + k * (DM / 2) + (i < 32 ? grp * 32 + i : 224 + grp * 8 + i));
                }
            }
            mbar_arrive(routed);
        } else if (warp == 11) {
            const uint32_t ep = sc->epoch[blockIdx.x] + 1;
            const uint32_t unit = lane < 16 ? lane >> 3 : (lane >> 1) - 6;
            const uint32_t ofs = (lane & 1) * 8192 + (lane < 16 ? ((lane >> 1) & 3) * 2048 : 0);
            if (lane < 18) mbar_expect_tx(rfull + 8 * lane, 8192);
            mbar_wait_sleep(soon, 0);
            uint32_t done = lane >= 30;
            do {
                if (!done) {
                    uint4 v;
                    asm volatile("ld.relaxed.gpu.global.v4.u32 {%0, %1, %2, %3}, [%4];" : "=r"(v.x), "=r"(v.y), "=r"(v.z), "=r"(v.w)
                                 : "l"(sc->flag + (qt * 8 + grp) * 32 + lane) : "memory");
                    uint32_t ok = v.x == ep && v.y == ep && v.z == ep && v.w == ep;
                    if (ok)
                        asm volatile("{\n.reg .pred p;\nmbarrier.test_wait.parity.shared::cta.b64 p, [%1], 0;\nselp.u32 %0, 1, 0, p;\n}\n"
                                     : "=r"(ok) : "r"(unit >= 6 ? rdone + (lane - 24) * 8 : vacant) : "memory");
                    done = ok;
                    if (ok)
                        asm volatile("cp.async.bulk.shared::cluster.global.mbarrier::complete_tx::bytes [%0], [%1], %2, [%3];"
                                     ::"r"(stash + (unit >= 6 ? unit - 6 : unit) * 16384 + ofs),
                                       "l"((const char*)sc->part + ((qt * 8 + grp) * 9 + unit) * 16384 + ofs), "r"(lane < 16 ? 2048 : 8192),
                                       "r"(rfull + 16 * unit + 8 * (lane & 1)) : "memory");
                }
            } while (!__all_sync(0xffffffffu, done));
        }
    } else {
        asm volatile("setmaxnreg.inc.sync.aligned.u32 240;");
        const uint32_t lane = threadIdx.x & 31;
        PT(2);
        asm volatile("barrier.cluster.wait.aligned;" ::: "memory");
        PT(3);
        const int my_bar = 1 + wg, other_bar = 2 - wg;
        const uint32_t my_stash = stash + warp * 4096 + lane * 16;
        constexpr uint32_t T16 = TILE_BYTES / 16;
        constexpr uint32_t ring16 = RING_OFFSET >> 4;
        uint32_t rel = 0;
        if (lane < 2)
            asm("mapa.shared::cluster.u32 %0, %1, %2;" : "=r"(rel) : "r"(empty), "r"(lane));
        rel = opaque(rel);

        const int zero = gridDim.y - 1;
        PT(4);

        uint32_t q[32];
        float acc[64];
        float wsum;
        uint32_t ep_tag;
        uint2 st0, st1;
        auto project = [&](auto helper_c, int job) {
            constexpr bool HELPER = decltype(helper_c)::value;
            float (&acc32)[32] = *reinterpret_cast<float (*)[32]>(&acc[0]);
            const int tile = qt + job;
            uint32_t lane = threadIdx.x & 31;
            if (HELPER) asm volatile("mov.u32 %0, %%laneid;" : "=r"(lane));
            uint32_t xa[128];
            const uint32_t lm_off = wg * 16384 + ((warp & 3) * 16 + (lane & 15)) * 128 + (((lane >> 4) ^ (lane & 7)) << 4);
            float sm[4][4] = {}, sq[4][4] = {};
            constexpr uint32_t ONES = 0x3f803f80u;
            constexpr float SC = 0.08838834764831845f * 1.4426950408889634f;
            auto squares = [&](const uint32_t* a) {
#pragma unroll
                for (int r = 0; r < 4; r++) hmma8(sq[r], a[r & 2], a[(r & 2) + 1], a[r]);
            };
            const int row = tile * 128 + warp * 16 + (lane >> 2);
            auto load_stats = [&](int t) {
                asm volatile("ld.relaxed.gpu.global.v2.u32 {%0, %1}, [%4];\nld.relaxed.gpu.global.v2.u32 {%2, %3}, [%4 + 64];"
                             : "=r"(st0.x), "=r"(st0.y), "=r"(st1.x), "=r"(st1.y) : "l"(sc->stat + t * 128 + warp * 16 + (lane >> 2)) : "memory");
            };
            uint32_t mm0, mm1;
            float rd0, rd1;
            if (HELPER && job == 0) load_stats(tile);
#pragma unroll
            for (int i = 0; i < 5; i++) {
                mbar_wait(xfull + (wg * 5 + i) * 8, HELPER ? job & 1 : 0);
                if (i == 0) PT(5);
                if (HELPER && i == 0) TR(20 + job * 8);
                if (HELPER && i == 4) TR(20 + job * 8 + 7);
                if (HELPER && job == 1) TR(110 + i);
                const uint32_t base = ring + (i == 4 ? 2 : 3 + i) * TILE_BYTES + lm_off;
                uint32_t* a = xa + (i == 0 ? 96 : 32 * (i - 1));
#pragma unroll
                for (int ks = 0; ks < 8; ks++)
                    ldsm4((base ^ ((ks & 3) << 5)) + (ks >> 2) * 8192, a[4 * ks], a[4 * ks + 1], a[4 * ks + 2], a[4 * ks + 3]);
                if (i == 4) PT(9);
                uint32_t wb[16];
#pragma unroll
                for (int ks = 0; ks < 8; ks++) {
                    wb[2 * ks] = ONES; wb[2 * ks + 1] = ONES;
                    if (HELPER)
                        asm volatile("ld.shared.v2.u32 {%0, %1}, [%2];" : "=r"(wb[2 * ks]), "=r"(wb[2 * ks + 1]) : "r"(wperm + (lane & 3) * 8 + ((i == 0 ? 32 : 8 * i - 8) + ks) * 32));
                }
#pragma unroll
                for (int ks = 0; ks < 8; ks++) {
                    hmma(sm[ks & 3], a[4 * ks], a[4 * ks + 1], a[4 * ks + 2], a[4 * ks + 3], wb[2 * ks], wb[2 * ks + 1]);
                    if (!HELPER && i < 4) squares(a + 4 * ks);
                }
                if (HELPER && i == 0) {
                    while (__any_sync(0xffffffffu, ((st0.x ^ ep_tag) | (st1.x ^ ep_tag)) >> 16)) load_stats(tile);
                    mm0 = __byte_perm(st0.x, 0, 0x1010); mm1 = __byte_perm(st1.x, 0, 0x1010);
#pragma unroll
                    for (int ks = 0; ks < 8; ks++)
                        stsm4((base ^ ((ks & 3) << 5)) + (ks >> 2) * 8192, bf2_sub(a[4 * ks], mm0), bf2_sub(a[4 * ks + 1], mm1),
                              bf2_sub(a[4 * ks + 2], mm0), bf2_sub(a[4 * ks + 3], mm1));
                    asm volatile("fence.proxy.async.shared::cta;" ::: "memory");
                }
            }
            release_at<16>(rel);
            sched_fence(zero);
            const float m0 = ((sm[0][0] + sm[1][0]) + (sm[2][0] + sm[3][0])) * (HELPER ? 1.f : 1.f / DM);
            const float m1 = ((sm[0][2] + sm[1][2]) + (sm[2][2] + sm[3][2])) * (HELPER ? 1.f : 1.f / DM);
            if (HELPER) {
                const float id0 = __uint_as_float(st0.y), id1 = __uint_as_float(st1.y);
                rd0 = SC * id0; rd1 = SC * id1;
                if ((lane & 3) == 0) {
                    sc->r[row] = bf_round((m0 - bf_lo(mm0) * wsum) * id0);
                    sc->r[row + 8] = bf_round((m1 - bf_lo(mm1) * wsum) * id1);
                }
                __syncwarp();
                if (job == 3 && lane == 0) mbar_arrive(qdone + 40);
            } else {
                mm0 = pack_bf16(m0, m0); mm1 = pack_bf16(m1, m1);
            }
            auto centre = [&](int kt) {
#pragma unroll
                for (int i = 32 * kt; i < 32 * kt + 32; i++) asm volatile("sub.rn.bf16x2 %0, %0, %1;" : "+r"(xa[i]) : "r"((i & 1) ? mm1 : mm0));
            };
            if (!HELPER) {
#pragma unroll
                for (int ks = 0; ks < 8; ks++) squares(xa + 96 + 4 * ks);
            }
            if (!HELPER) centre(0);
            if (wg == 1) bar_arrive(1);
            auto diag = [&](int r, int h) { return (lane & 4) ? sq[r][h + 1] + sq[r + 2][h + 1] : sq[r][h] + sq[r + 2][h]; };
            auto spread = [&](float v) { return __shfl_sync(0xffffffffu, v, (lane & ~3u) | (lane >> 3)) * (1.f / DM); };
            if (!HELPER) { rd0 = diag(0, 0); rd1 = diag(1, 2); }
            PT(10);

            if (HELPER) TR(20 + job * 8 + 1);
            uint32_t qs = 0, qph = HELPER ? job & 1 : 0;
            uint4 gx;
            if (HELPER) {
#pragma unroll
                for (int i = 0; i < 64; i++) acc[i] = 0.f;
            }
            const uint32_t xs16 = ring16 + 3 * T16 + wg * 1024;
            constexpr int SS = HELPER ? 0 : 3;
            auto finish_stats = [&] {
                float v0 = spread(rd0) - m0 * m0, v1 = spread(rd1) - m1 * m1;
                if (__any_sync(0xffffffffu, !(m0 * m0 <= 256.f * v0 && m1 * m1 <= 256.f * v1))) {
                    const uint4* xr = (const uint4*)x + row * (DM / 8) + (lane & 3);
                    v0 = 0.f; v1 = 0.f;
#pragma unroll 1
                    for (int i = 0; i < DM / 32; i++) {
                        const uint4 a = __ldg(xr + 4 * i), b = __ldg(xr + DM + 4 * i);
                        const uint32_t w[8] = {a.x, a.y, a.z, a.w, b.x, b.y, b.z, b.w};
#pragma unroll
                        for (int k = 0; k < 8; k++) {
                            const uint32_t d = bf2_sub(w[k], k < 4 ? mm0 : mm1);
                            float& v = k < 4 ? v0 : v1;
                            v = fmaf(bf_lo(d), bf_lo(d), fmaf(bf_hi(d), bf_hi(d), v));
                        }
                    }
#pragma unroll
                    for (int d = 1; d <= 2; d <<= 1) { v0 += __shfl_xor_sync(0xffffffffu, v0, d); v1 += __shfl_xor_sync(0xffffffffu, v1, d); }
                    v0 *= 1.f / DM; v1 *= 1.f / DM;
                    const float e0 = m0 - bf_lo(mm0), e1 = m1 - bf_lo(mm1);
                    v0 -= e0 * e0; v1 -= e1 * e1;
                }
                const float id0 = inv_den(fmaxf(v0, 0.f)), id1 = inv_den(fmaxf(v1, 0.f));
                rd0 = SC * id0; rd1 = SC * id1;
                if (warp == grp) {
                    mbar_wait(epv, 0);
                    uint32_t tg;
                    asm volatile("ld.shared.u32 %0, [%1];" : "=r"(tg) : "r"(epoch));
                    if ((lane & 3) == 0)
                        asm volatile("st.relaxed.gpu.global.v2.u32 [%0], {%1, %2};\nst.relaxed.gpu.global.v2.u32 [%0 + 64], {%3, %4};"
                                     ::"l"(sc->stat + row), "r"(__byte_perm(mm0, tg, 0x5410)), "f"(id0), "r"(__byte_perm(mm1, tg, 0x5410)), "f"(id1) : "memory");
                }
            };
#pragma unroll 1
            for (int pass = 0;; pass++) {
                const uint32_t hs = my_stash + (pass == 2 ? 0 : pass + 1) * TILE_BYTES;
                uint4* const dst = sc->qoff + ((tile * 4 + pass) * 8 + warp) * 256 + lane;
                auto put = [&](int lo) {
#pragma unroll
                    for (int i = lo; i < lo + 4; i++) {
                        const uint4 v = make_uint4(pack_bf16(acc[8 * i] * rd0, acc[8 * i + 1] * rd0), pack_bf16(acc[8 * i + 2] * rd1, acc[8 * i + 3] * rd1),
                                                   pack_bf16(acc[8 * i + 4] * rd0, acc[8 * i + 5] * rd0), pack_bf16(acc[8 * i + 6] * rd1, acc[8 * i + 7] * rd1));
                        if (HELPER) dst[i * 32] = v;
                        else sts128(hs + i * 512, v.x, v.y, v.z, v.w);
                        if (i == 3) sched_fence(zero);
                    }
                };
                auto gate_load = [&](int j) {
                    const uint32_t* src = (const uint32_t*)x + (qt * 128 + warp * 16 + (lane >> 2)) * (DM / 2) + (lane & 3) +
                                          (j < 4 ? grp * 32 + j * 8 : 256 + grp * 8);
                    asm volatile("ld.global.nc.u32 %0, [%4];\nld.global.nc.u32 %1, [%4 + %5];\n"
                                 "ld.global.nc.u32 %2, [%4 + 16];\nld.global.nc.u32 %3, [%4 + %5 + 16];"
                                 : "=r"(gx.x), "=r"(gx.y), "=r"(gx.z), "=r"(gx.w) : "l"(src), "n"(8 * DM * 2));
                };
                auto gate_store = [&](int j) {
                    const float id0 = rd0 * (1.f / SC), id1 = rd1 * (1.f / SC);
                    uint4* g = sc->gate + (blockIdx.x * 5 + j) * 512 + threadIdx.x;
                    g[0] = gx;
                    g[256] = make_uint4(silu2_ln(normalise(gx.x, mm0, id0)), silu2_ln(normalise(gx.y, mm1, id1)),
                                        silu2_ln(normalise(gx.z, mm0, id0)), silu2_ln(normalise(gx.w, mm1, id1)));
                };
                auto advance = [&] {
                    const uint32_t r = rel ? rel + 8 * qs : 0;
                    if (++qs == 2) qph ^= 1;
                    if (qs == 3) qs = 0;
                    return r;
                };
                if (!HELPER && pass == 1) {
#pragma unroll
                    for (int turn = 0; turn < 3; turn++) {
                        if (turn) mbar_wait(full + 8 * qs, qph);
                        bar_sync(my_bar);
                        const uint32_t tile16 = ring16 + qs * T16;
                        wg_fence();
#pragma unroll
                        for (int ks = 0; ks < (turn == 1 ? 8 : 16); ks++) {
                            const uint32_t* a = xa + (turn == 2 ? 64 : turn * 64) + 4 * ks;
                            if (turn == 2 && ks < 8) wgmma_ss64(acc32, desc_kmajor(xs16 - (ks >> 2) * 512, ks), desc_nmajor(tile16, ks), 1);
                            else wgmma_rs64(acc32, a[0], a[1], a[2], a[3], desc_nmajor(tile16, ks), turn || ks);
                        }
                        wg_commit();
                        bar_arrive(other_bar);
                        const uint32_t rl = advance();
                        if (turn == 2) mbar_wait(full + 8 * qs, qph);
                        wg_wait<0>();
                        TA(5 + 2 * turn);
                        release_at<0>(rl);
                    }
                    pin(acc32);
                    put(0);
                    continue;
                }
                uint32_t rl = 0;
#pragma unroll
                for (int kt = 0; kt < 5; kt++) {
                    const bool takes = !HELPER || kt == 0 || kt == 2 || kt == 3, passes = !HELPER || kt == 1 || kt == 2 || kt == 4;
                    if (kt != 0 || pass == 0) mbar_wait(full + 8 * qs, qph);
                    if (takes) bar_sync(my_bar);
                    const uint32_t tile16 = ring16 + qs * T16;
                    wg_fence();
                    if (kt != SS) {
                        mma_tile<1>(acc, xa + (kt < SS ? kt : kt - 1) * 32, tile16, kt != 0);
                    } else {
#pragma unroll
                        for (int ks = 0; ks < 8; ks++) wgmma_ss(acc, desc_kmajor(xs16 - (ks >> 2) * 512, ks), desc_nmajor(tile16, ks), kt || ks);
                        wg_commit();
                    }
                    if (passes && !(HELPER && kt == 4 && pass == 3 && wg == 1)) bar_arrive(other_bar);
                    if (HELPER && pass == 0 && kt < 4) centre(kt);
                    if (!HELPER && pass == 0 && kt < 3) {
#pragma unroll
                        for (int ks = 3 * kt; ks < 3 * kt + 3 && ks < 8; ks++) {
                            const uint32_t ad = ((ring + 3 * TILE_BYTES + lm_off) ^ ((ks & 3) << 5)) + (ks >> 2) * 8192;
                            uint32_t a, b, c, d;
                            ldsm4(ad, a, b, c, d);
                            stsm4(ad, bf2_sub(a, mm0), bf2_sub(b, mm1), bf2_sub(c, mm0), bf2_sub(d, mm1));
                        }
                        if (kt == 2) asm volatile("fence.proxy.async.shared::cta;" ::: "memory");
                    }
                    if (!HELPER && pass == 0 && kt == FINK) finish_stats();
                    if (HELPER && kt == 2 && pass == 3 && job < 3) load_stats(tile + 1);
                    if (!HELPER && pass >= 2 && kt < 4) {
                        if (kt & 1) gate_store((pass - 2) * 2 + (kt >> 1));
                        else gate_load((pass - 2) * 2 + (kt >> 1));
                    }
                    if (!HELPER && pass == G4 && kt == 3) gate_load(4);
                    if (!HELPER && pass == G4 && kt == 4) gate_store(4);
                    const uint32_t rl_prev = rl;
                    rl = advance();
                    if (!passes) continue;
                    if (HELPER && kt != 2) {
                        wg_wait<1>();
                        if (job == 1) TR(120 + pass * 5 + kt - 1);
                        release_at<0>(rl_prev);
                        if (kt == 1 && pass == 3) release_at<24>(rel);
                    }
                    if (kt == 4 && !(HELPER && pass == 3)) mbar_wait(full + 8 * qs, qph);
                    wg_wait<0>();
                    if (!HELPER) TA(pass * 5 + kt);
                    if (HELPER && job == 1) TR(120 + pass * 5 + kt);
                    release_at<0>(rl);
                    if (!HELPER && kt < 3 && pass == 0) centre(kt + 1);
                }
                pin(acc);
                if (!HELPER && pass == 3) break;
                put(0);
                put(4);
                if (HELPER) TR(20 + job * 8 + 2 + pass);
                if (HELPER && pass == 3) {
                    __syncwarp();
                    if (lane == 0) mbar_arrive(qdone + 8 * job);
                    return;
                }
            }
            release_at<24>(rel);
            if (lane == 0) mbar_arrive(gated);
#pragma unroll
            for (int i = 0; i < 32; i++) {
                const float r = (i & 1) ? rd1 : rd0;
                q[i] = pack_bf16(acc[2 * i] * r, acc[2 * i + 1] * r);
            }
        };
        if (helper) {
            const uint32_t ep = sc->epoch[blockIdx.x] + 1;
            if (threadIdx.x < 160) {
                const uint32_t* w32 = (const uint32_t*)wr + (threadIdx.x >> 2) * 8 + (threadIdx.x & 3);
                asm volatile("st.shared.v2.u32 [%0], {%1, %2};" ::"r"(wperm + threadIdx.x * 8), "r"(__ldg(w32)), "r"(__ldg(w32 + 4)) : "memory");
            }
            asm volatile("bar.sync 3, 256;" ::: "memory");
            float ws[4] = {};
#pragma unroll 4
            for (int ks = 0; ks < 40; ks++) {
                uint32_t b0, b1;
                asm volatile("ld.shared.v2.u32 {%0, %1}, [%2];" : "=r"(b0), "=r"(b1) : "r"(wperm + (lane & 3) * 8 + ks * 32));
                hmma(ws, 0x3f803f80u, 0x3f803f80u, 0x3f803f80u, 0x3f803f80u, b0, b1);
            }
            wsum = ws[0];
            ep_tag = ep << 16;
            TR(0);
#pragma unroll 1
            for (int job = 0; job < 4; job++) {
                project(cint<1>(), job);
                TR(1 + job);
            }
            if (elect_one()) mbar_arrive(h1done);
            ffn_role(sc, ring, ffull, fempty, alldone, blockIdx.x - N_MAIN, ep, warp, x);
            return;
        }
        project(cint<0>(), 0);
        TRM(2);
        TG(112);

        float o[64];
        uint32_t p[32];
        float l0, l1;
        constexpr float L_LO = 9.313225746154785e-10f, L_HI = 1.152921504606847e18f;
        float l_hi = L_HI;
        float (&s)[64] = acc;

        auto exp_range = [&](const float (&s)[64], int lo, int hi, float& u0, float& u1) {
            float w0 = 0.f, w1 = 0.f;
#pragma unroll
            for (int i = lo; i < hi; i += 4) {
                const float e0 = ex2(s[i]), e1 = ex2(s[i + 1]), e2 = ex2(s[i + 2]), e3 = ex2(s[i + 3]);
                u0 += e0; u1 += e2;
                if (i == lo) { w0 = e1; w1 = e3; } else { w0 += e1; w1 += e3; }
                p[i / 2] = pack_bf16(e0, e1); p[i / 2 + 1] = pack_bf16(e2, e3);
            }
            u0 += w0; u1 += w1;
        };
        auto unsafe = [&](bool first, float u0, float u1) {
            return (bool)__any_sync(0xffffffffu, !(u0 + u1 <= l_hi) || (first && !(fminf(u0, u1) >= L_LO)));
        };
        auto softmax_true_max = [&](const float (&s)[64], bool first, float b0, float b1, float& u0, float& u1) {
            uint32_t t;
            asm volatile("mov.u32 %0, %%tid.x;" : "=r"(t));
            uint4* const st = sc->rare + blockIdx.x * (17 * 256) + t;
            auto ld = [](const uint4* a) {
                uint4 v;
                asm volatile("ld.global.v4.u32 {%0, %1, %2, %3}, [%4];" : "=r"(v.x), "=r"(v.y), "=r"(v.z), "=r"(v.w) : "l"(a) : "memory");
                return v;
            };
#pragma unroll
            for (int i = 0; i < 16; i++)
                asm volatile("st.global.v4.f32 [%0], {%1, %2, %3, %4};" ::"l"(st + i * 256), "f"(s[4 * i]), "f"(s[4 * i + 1]), "f"(s[4 * i + 2]), "f"(s[4 * i + 3]) : "memory");
            float a0 = s[0], a1 = s[2];
#pragma unroll 1
            for (int i = 0; i < 16; i++) {
                const uint4 v = ld(st + i * 256);
                a0 = fmaxf(a0, fmaxf(__uint_as_float(v.x), __uint_as_float(v.y)));
                a1 = fmaxf(a1, fmaxf(__uint_as_float(v.z), __uint_as_float(v.w)));
            }
            float t0 = b0, t1 = b1, sg0 = 0.f, sg1 = 0.f;
            if (l_hi < 0.f) {
                const uint4 v = ld(st + 16 * 256);
                sg0 = __uint_as_float(v.x); sg1 = __uint_as_float(v.y);
            }
#pragma unroll
            for (int d = 1; d <= 2; d <<= 1) {
                a0 = fmaxf(a0, __shfl_xor_sync(0xffffffffu, a0, d)); a1 = fmaxf(a1, __shfl_xor_sync(0xffffffffu, a1, d));
                t0 += __shfl_xor_sync(0xffffffffu, t0, d); t1 += __shfl_xor_sync(0xffffffffu, t1, d);
            }
            if (!first) {
                a0 = fmaxf(a0, l_hi < 0.f ? sg0 : __log2f(t0)); a1 = fmaxf(a1, l_hi < 0.f ? sg1 : __log2f(t1));
            }
            const float al0 = first ? 1.f : ex2(sg0 - a0), al1 = first ? 1.f : ex2(sg1 - a1);
            asm volatile("st.global.v2.f32 [%0], {%1, %2};" ::"l"(st + 16 * 256), "f"(a0), "f"(a1) : "memory");
            l_hi = -1.f;
            u0 = b0 * al0; u1 = b1 * al1;
#pragma unroll 1
            for (int i = 0; i < 16; i++) {
                const uint4 v = ld(st + i * 256);
                const float e0 = ex2(__uint_as_float(v.x) - a0), e1 = ex2(__uint_as_float(v.y) - a0);
                const float e2 = ex2(__uint_as_float(v.z) - a1), e3 = ex2(__uint_as_float(v.w) - a1);
                u0 += e0 + e1; u1 += e2 + e3;
                asm volatile("st.global.v2.u32 [%0], {%1, %2};" ::"l"((uint2*)(st + (i >> 1) * 256) + (i & 1)), "r"(pack_bf16(e0, e1)), "r"(pack_bf16(e2, e3)) : "memory");
            }
#pragma unroll
            for (int i = 0; i < 8; i++) {
                const uint4 v = ld(st + i * 256);
                p[4 * i] = v.x; p[4 * i + 1] = v.y; p[4 * i + 2] = v.z; p[4 * i + 3] = v.w;
            }
            if (&s != &o) {
#pragma unroll
                for (int i = 0; i < 64; i++) o[i] *= (i & 2) ? al1 : al0;
            }
        };
        auto inv_sums = [&](float& i0, float& i1) {
            float a = l0, b = l1;
            a += __shfl_xor_sync(0xffffffffu, a, 1); b += __shfl_xor_sync(0xffffffffu, b, 1);
            a += __shfl_xor_sync(0xffffffffu, a, 2); b += __shfl_xor_sync(0xffffffffu, b, 2);
            i0 = rcp(a); i1 = rcp(b);
        };

        {
            bar_sync(my_bar);
            wg_fence();
            mma_tile<0>(o, q, ring16, 0);
            mbar_wait(full + 8, 0);
            wg_fence();
            mma_tile<0>(s, q, ring16 + T16, 0);
            bar_arrive(other_bar);
            wg_wait<1>();
            TA(20);
            release_at<0>(rel);
            pin(o);
            l0 = 0.f; l1 = 0.f;
            exp_range(o, 0, 64, l0, l1);
            mbar_wait(full + 16, 1);
            wg_wait<0>();
            if (unsafe(true, l0, l1)) softmax_true_max(o, true, 0.f, 0.f, l0, l1);
        }
        uint32_t qsrc = my_stash;
        float il0 = 0.f, il1 = 0.f;
        auto step = [&](auto odd_c, int m) {
            constexpr int ODD = decltype(odd_c)::value;
            constexpr int KS = ODD ? 3 : 1, VS = ODD ? 0 : 2;
            constexpr int SP = ODD ? SPLITO : SPLIT;
            [[maybe_unused]] const int it = 2 * m + ODD;
            const uint32_t ph = m & 1;
            TC(0);
            bar_sync(my_bar);
            TC(1);
            if (ODD || m) {
                wg_fence();
                mma_tile<0>(s, q, ring16 + KS * T16, 0);
            }
            TC(2);
            if (!ODD) {
                if ((m & 7) == 0 && m) {
#pragma unroll
                    for (int i = FSPLIT; i < 8; i++)
                        sts128(qsrc + i * 512,
                               pack_bf16(o[8 * i] * il0, o[8 * i + 1] * il0), pack_bf16(o[8 * i + 2] * il1, o[8 * i + 3] * il1),
                               pack_bf16(o[8 * i + 4] * il0, o[8 * i + 5] * il0), pack_bf16(o[8 * i + 6] * il1, o[8 * i + 7] * il1));
                    qsrc += m == 24 ? -2 * TILE_BYTES : TILE_BYTES;
                }
                wg_fence();
            }
#pragma unroll
            for (int ks = 0; ks < 8; ks++) {
                wgmma_rs<1>(o, p[4 * ks], p[4 * ks + 1], p[4 * ks + 2], p[4 * ks + 3], desc_nmajor(ring16 + VS * T16, ks),
                            (ks == 0 && !ODD) ? ((m & 7) != 0) : 1);
                if (ks == SP / 8 - 1 || ks == 7) wg_commit();
            }
            TC(3);
            bar_arrive(other_bar);
            const bool last = ODD && (m & 7) == 7;
            if (last) {
                inv_sums(il0, il1);
                l0 = 0.f; l1 = 0.f; l_hi = L_HI;
            }
            wg_wait<1>();
            TA(21 + it);
            TC(4);
            release_at<8 * KS>(rel);
            const bool newq = (m & 7) == 7;
            if (!ODD) {
                lds128_if<0>(newq, qsrc, q[0], q[1], q[2], q[3]);
                lds128_if<512>(newq, qsrc, q[4], q[5], q[6], q[7]);
            }
            pin(s);
            float u0 = l0, u1 = l1;
            exp_range(s, 0, SP, u0, u1);
            mbar_wait_hot(full + 8 * (KS ^ 2), ph ^ 1);
            if (!ODD) {
                lds128_if<1024>(newq, qsrc, q[8], q[9], q[10], q[11]);
                lds128_if<1536>(newq, qsrc, q[12], q[13], q[14], q[15]);
                lds128_if<2048>(newq, qsrc, q[16], q[17], q[18], q[19]);
            }
            TC(5);
            wg_wait<0>();
            release_at<8 * VS>(rel);
            pin(o);
            exp_range(s, SP, 64, u0, u1);
            TC(6);
            mbar_wait_hot(full + 8 * (VS ^ 2), ODD ? ph : ph ^ 1);
            if (!ODD) {
                lds128_if<2560>(newq, qsrc, q[20], q[21], q[22], q[23]);
                lds128_if<3072>(newq, qsrc, q[24], q[25], q[26], q[27]);
                lds128_if<3584>(newq, qsrc, q[28], q[29], q[30], q[31]);
            } else if (last) {
#pragma unroll
                for (int i = 0; i < FSPLIT; i++)
                    sts128(qsrc + i * 512,
                           pack_bf16(o[8 * i] * il0, o[8 * i + 1] * il0), pack_bf16(o[8 * i + 2] * il1, o[8 * i + 3] * il1),
                           pack_bf16(o[8 * i + 4] * il0, o[8 * i + 5] * il0), pack_bf16(o[8 * i + 6] * il1, o[8 * i + 7] * il1));
            }
            if (unsafe(last, u0, u1)) softmax_true_max(s, last, l0, l1, u0, u1);
            l0 = u0; l1 = u1;
            TC(7);
            TF(3 + it);
        };
#pragma unroll 1
        for (int m = 0;; m++) {
            step(cint<0>(), m);
            if (m == 31) break;
            step(cint<1>(), m);
        }
        uint32_t ob[64];
        const uint32_t t128 = threadIdx.x & 127;
        uint32_t ep, tag;
        const uint32_t half = 0x8000u;
        auto send = [&](uint4* dst, const float* a) {
            asm volatile("st.relaxed.gpu.global.v4.u32 [%0], {%1, %2, %3, %4};" ::"l"(dst), "r"(lop3<0xD8>(pack_bf16(a[0], a[1]), tag, 0x10000u)),
                         "r"(pack_bf16(a[2], a[3])), "r"(pack_bf16(a[4], a[5])), "r"(pack_bf16(a[6], a[7])) : "memory");
        };
        auto hint = [&](int dst, int job) {
            asm volatile("st.relaxed.gpu.global.u32 [%0], %1;" ::"l"((uint32_t*)(sc->flag + (qt * 8 + dst) * 32 + job) + (warp & 3)), "r"(ep) : "memory");
        };
        float a32[32], own[32];
        auto half_mma = [&](const uint32_t* a, const uint32_t* b, uint32_t t16, int accumulate) {
            wg_fence();
#pragma unroll
            for (int ks = 0; ks < 8; ks++) wgmma_rs64(a32, a[4 * ks], a[4 * ks + 1], a[4 * ks + 2], a[4 * ks + 3], desc_nmajor(t16, ks), ks ? 1 : accumulate);
#pragma unroll
            for (int ks = 0; ks < 8; ks++) wgmma_rs64(a32, b[4 * ks], b[4 * ks + 1], b[4 * ks + 2], b[4 * ks + 3], desc_nmajor(t16, 8 + ks), 1);
            wg_commit();
        };
        auto block_mma = [&](uint32_t sb, uint32_t ph, bool pass_turn) {
            mbar_wait(full + 8 * sb, ph);
            bar_sync(my_bar);
            half_mma(q, ob, ring16 + sb * T16, zero);
            mbar_wait(full + 8 * sb + 8, ph);
            half_mma(ob + 32, p, ring16 + (sb + 1) * T16, 1);
            if (pass_turn) bar_arrive(other_bar);
        };
        auto send_strips = [&](int u) {
            const uint32_t t = opaque(t128);
            const int d0 = (grp & 4) ^ (4 * u);
            uint4* dst = sc->part + (((qt * 8 + d0) * 9 + u) * 2 + wg) * 512 + (grp & 3) * 128 + t;
#pragma unroll
            for (int i = 0; i < 4; i++) send(dst + i * 9 * 1024, a32 + 8 * i);
            if ((t & 31) < 4) hint(d0 + (t & 31), u * 8 + (grp & 3) * 2 + wg);
        };
        uint32_t xs[4], gs[4];
        {
            [[maybe_unused]] const int c = 9;
            TS(0);
            auto fetch_o = [&](int lo, int hi) {
#pragma unroll
                for (int i = lo; i < hi; i++)
                    lds128(qsrc + (1 + (i >> 3)) * TILE_BYTES + (i & 7) * 512, ob[4 * i], ob[4 * i + 1], ob[4 * i + 2], ob[4 * i + 3]);
            };
            fetch_o(0, 3);
            bar_sync(my_bar);
            wg_fence();
            mma_tile<1>(o, p, ring16 + 3 * T16, 1);
            sched_fence(zero);
            inv_sums(il0, il1);
            asm volatile("" : "+f"(il0), "+f"(il1));
            sched_fence(zero);
            fetch_o(3, 6);
            wg_fence();
#pragma unroll
            for (int ks = 0; ks < 8; ks++) {
                wgmma_rs64(a32, q[4 * ks], q[4 * ks + 1], q[4 * ks + 2], q[4 * ks + 3], desc_nmajor(ring16, ks), ks);
                if (ks == 3) { wg_commit(); sched_fence(zero); fetch_o(6, 8); wg_fence(); }
            }
            TS(1);
#pragma unroll
            for (int ks = 0; ks < 8; ks++) wgmma_rs64(a32, ob[4 * ks], ob[4 * ks + 1], ob[4 * ks + 2], ob[4 * ks + 3], desc_nmajor(ring16, 8 + ks), 1);
            wg_commit();
            TS(2);
            bar_arrive(other_bar);
            wg_wait<1>();
            release_at<24>(rel);
            pin(o);
#pragma unroll
            for (int i = 0; i < 32; i++) {
                const float r = (i & 1) ? il1 : il0;
                asm volatile("cvt.rn.bf16x2.f32 %0, %1, %2;" : "=r"(p[i]) : "f"(o[2 * i + 1] * r), "f"(o[2 * i] * r));
                if ((i & 7) == 7) fetch_o(8 + (i >> 3) * 2, 10 + (i >> 3) * 2);
            }
            TS(3);
            mbar_wait(full + 8, 0);
            wg_wait<0>();
            release_at<0>(rel);
            __syncwarp();
            if (lane == 0) mbar_arrive(vacant);
            TS(4);
            bar_sync(my_bar);
            half_mma(ob + 32, p, ring16 + T16, 1);
            TS(5);
            bar_arrive(other_bar);
            TRM(66);
            TG(113);
            mbar_wait(routed, 0);
            asm volatile("ld.shared.u32 %0, [%1];" : "=r"(ep) : "r"(epoch));
            tag = ep << 16;
            const uint4* src = sc->gate + (blockIdx.x * 5 + 4) * 512 + threadIdx.x;
            asm volatile("ld.global.cg.v4.u32 {%0, %1, %2, %3}, [%4];" : "=r"(xs[0]), "=r"(xs[1]), "=r"(xs[2]), "=r"(xs[3]) : "l"(src));
            asm volatile("ld.global.cg.v4.u32 {%0, %1, %2, %3}, [%4];" : "=r"(gs[0]), "=r"(gs[1]), "=r"(gs[2]), "=r"(gs[3]) : "l"(src + 256));
            sched_fence(zero);
            wg_wait<0>();
            TS(6);
            release_at<8>(rel);
            pin(a32);
            send_strips(0);
            TS(7);
        }
        uint32_t v[4][4];
        auto stale = [&]() {
            return __any_sync(0xffffffffu, lop3<0xA8>(lop3<0x7E>(v[0][0], v[1][0], tag), lop3<0x7E>(v[2][0], v[3][0], tag), 0x10000u));
        };
        auto recv = [&](int u) {
            mbar_wait(rfull + 16 * u + 8 * wg, 0);
#pragma unroll
            for (int i = 0; i < 4; i++)
                lds128(stash + (u >= 6 ? u - 6 : u) * 16384 + wg * 8192 + i * 2048 + t128 * 16, v[i][0], v[i][1], v[i][2], v[i][3]);
            if (stale()) {
                const uint4* src = sc->part + (((qt * 8 + grp) * 9 + u) * 2 + wg) * 512 + opaque(t128);
                do {
#pragma unroll
                    for (int i = 0; i < 4; i++)
                        asm volatile("ld.relaxed.gpu.global.v4.u32 {%0, %1, %2, %3}, [%4];" : "=r"(v[i][0]), "=r"(v[i][1]), "=r"(v[i][2]), "=r"(v[i][3])
                                     : "l"(src + i * 128) : "memory");
                } while (stale());
            }
            if (u < 3 && lane == 0) mbar_arrive(rdone + (u * 2 + wg) * 8);
        };
        auto accumulate = [&](float* dst, int stride) {
#pragma unroll
            for (int i = 0; i < 4; i++) {
                float* a = dst + stride * i;
                a[0] += bf_lo(v[i][0]);
                a[1] += __uint_as_float(lop3<0xEC>(v[i][0], half, 0xfffe0000u));
#pragma unroll
                for (int k = 1; k < 4; k++) { a[2 * k] += bf_lo(v[i][k]); a[2 * k + 1] += bf_hi(v[i][k]); }
            }
        };
        auto gate = [](uint32_t x2, uint32_t g2, float lo, float hi) {
            uint32_t sv = pack_bf16(lo, hi);
            asm("mul.rn.bf16x2 %0, %0, %1;" : "+r"(sv) : "r"(g2));
            asm("add.rn.bf16x2 %0, %0, %1;" : "+r"(sv) : "r"(x2));
            return sv;
        };
        uint4* const outbox = sc->part + qt * (8 * 9 * 1024) + wg * 512 + t128;
        auto step_o = [&](int f) {
            [[maybe_unused]] const int c = f;
            const uint32_t sb = (f & 1) ? 0 : 2;
            block_mma(sb, (((f + 3) >> 1) ^ f) & 1, true);
            wg_wait<1>();
            const uint32_t rl = rel && f < 7 ? rel + 8 * sb : 0;
            release_at<0>(rl);
            if (f >= 1) recv(f - 1);
            wg_wait<0>();
            TS(0);
            release_at<8>(rl);
            pin(a32);
            if (f == 0) {
                send_strips(1);
            } else {
                const int d = (grp + f) & 7;
#pragma unroll
                for (int i = 0; i < 4; i++) send(outbox + (d * 9 + f + 1) * 1024 + i * 128, a32 + 8 * i);
                if (lane == 0) hint(d, 14 + 2 * f + wg);
            }
            TS(1);
        };
        {
            float st[8] = {};
#pragma unroll 1
            for (int f = 0; f < 3; f++) {
                [[maybe_unused]] const int c = f;
                step_o(f);
                if (f >= 1) accumulate(st, 0);
                TS(2);
            }
            uint32_t w[4];
#pragma unroll
            for (int i = 0; i < 4; i++) w[i] = gate(xs[i], gs[i], st[2 * i], st[2 * i + 1]);
            const bool odd = lane & 1;
            const uint32_t r0 = __shfl_xor_sync(0xffffffffu, odd ? w[0] : w[2], 1), r1 = __shfl_xor_sync(0xffffffffu, odd ? w[1] : w[3], 1);
            uint2* dst = (uint2*)out + (qt * 128 + warp * 16 + (lane >> 2)) * (DM / 4) + 128 + grp * 4 + (lane & 1) * 2 + ((lane >> 1) & 1);
            dst[0] = odd ? make_uint2(r0, w[2]) : make_uint2(w[0], r0);
            dst[2 * DM] = odd ? make_uint2(r1, w[3]) : make_uint2(w[1], r1);
        }
#pragma unroll
        for (int i = 0; i < 32; i++) own[i] = 0.f;
#pragma unroll 1
        for (int f = 3; f < 8; f++) {
            [[maybe_unused]] const int c = f;
            step_o(f);
            accumulate(own, 8);
            TS(2);
        }
        {
            [[maybe_unused]] const int c = 8;
            recv(7);
            accumulate(own, 8);
            TS(7);
            block_mma(2, 1, wg == 0);
            TRM(71);
            TS(0);
            recv(8);
            accumulate(own, 8);
            TS(1);
            wg_wait<1>();
            uint32_t xv[16], gv[16];
            mbar_wait(xgfull, 0);
            if (lane == 0) mbar_arrive(alldone);
#pragma unroll
            for (int j = 0; j < 4; j++) {
                lds128(stash + 3 * 16384 + j * 8192 + threadIdx.x * 16, xv[4 * j], xv[4 * j + 1], xv[4 * j + 2], xv[4 * j + 3]);
                lds128(stash + 3 * 16384 + j * 8192 + 4096 + threadIdx.x * 16, gv[4 * j], gv[4 * j + 1], gv[4 * j + 2], gv[4 * j + 3]);
            }
            TS(2);
            wg_wait<0>();
            pin(a32);
#pragma unroll
            for (int i = 0; i < 32; i++) own[i] += a32[i];
            TS(3);
            const uint32_t tb = ring + warp * 2048;
#pragma unroll
            for (int j = 0; j < 4; j++)
                stsm4(tb + (lane & 15) * 128 + (((2 * j + (lane >> 4)) ^ (lane & 7)) << 4),
                      gate(xv[4 * j], gv[4 * j], own[8 * j], own[8 * j + 1]), gate(xv[4 * j + 1], gv[4 * j + 1], own[8 * j + 2], own[8 * j + 3]),
                      gate(xv[4 * j + 2], gv[4 * j + 2], own[8 * j + 4], own[8 * j + 5]), gate(xv[4 * j + 3], gv[4 * j + 3], own[8 * j + 6], own[8 * j + 7]));
            __syncwarp();
#pragma unroll
            for (int j = 0; j < 4; j++) {
                const uint32_t row = j * 4 + (lane >> 3);
                uint4 v;
                lds128(tb + row * 128 + (((lane & 7) ^ (row & 7)) << 4), v.x, v.y, v.z, v.w);
                ((uint4*)out)[(qt * 128 + warp * 16 + row) * (DM / 8) + grp * 8 + (lane & 7)] = v;
            }
        }
        TRM(73);
        TG(111);
    }
}

typedef CUresult (*EncodeFn)(CUtensorMap*, CUtensorMapDataType, cuuint32_t, void*, const cuuint64_t*, const cuuint64_t*,
                             const cuuint32_t*, const cuuint32_t*, CUtensorMapInterleave, CUtensorMapSwizzle,
                             CUtensorMapL2promotion, CUtensorMapFloatOOBfill);

void make_map(EncodeFn enc, CUtensorMap* tm, const void* ptr, uint64_t cols, uint64_t rows) {
    cuuint64_t gd[2] = {cols, rows};
    cuuint64_t gs[1] = {cols * 2};
    cuuint32_t bd[2] = {64, 128};
    cuuint32_t es[2] = {1, 1};
    enc(tm, CU_TENSOR_MAP_DATA_TYPE_BFLOAT16, 2, const_cast<void*>(ptr), gd, gs, bd, es, CU_TENSOR_MAP_INTERLEAVE_NONE,
        CU_TENSOR_MAP_SWIZZLE_128B, CU_TENSOR_MAP_L2_PROMOTION_L2_256B, CU_TENSOR_MAP_FLOAT_OOB_FILL_NONE);
}

}

extern "C" void kernel_launch(void* const* d_in, const int* in_sizes, int n_in, void* d_out, int out_size) {
    const __nv_bfloat16* x = (const __nv_bfloat16*)d_in[0];
    const __nv_bfloat16* wr = (const __nv_bfloat16*)d_in[6];
    __nv_bfloat16* out = (__nv_bfloat16*)d_out;

    EncodeFn enc = nullptr;
    cudaDriverEntryPointQueryResult qr;
    cudaGetDriverEntryPoint("cuTensorMapEncodeTiled", (void**)&enc, cudaEnableDefault, &qr);
    CUtensorMap tm_x, tm_wq, tm_k, tm_v, tm_wo, tm_g, tm_u, tm_d;
    {
        cuuint64_t gd[3] = {64, SEQ, DM / 64};
        cuuint64_t gs[2] = {DM * 2, 128};
        cuuint32_t bd[3] = {64, 64, 2};
        cuuint32_t es[3] = {1, 1, 1};
        enc(&tm_x, CU_TENSOR_MAP_DATA_TYPE_BFLOAT16, 3, d_in[0], gd, gs, bd, es, CU_TENSOR_MAP_INTERLEAVE_NONE,
            CU_TENSOR_MAP_SWIZZLE_128B, CU_TENSOR_MAP_L2_PROMOTION_L2_256B, CU_TENSOR_MAP_FLOAT_OOB_FILL_NONE);
    }
    make_map(enc, &tm_k, d_in[1], DH, (uint64_t)NH * SEQ);
    make_map(enc, &tm_v, d_in[2], DH, (uint64_t)NH * SEQ);
    make_map(enc, &tm_wq, d_in[3], NH * DH, DM);
    make_map(enc, &tm_wo, d_in[4], DM, NH * DH);
    make_map(enc, &tm_g, d_in[7], FF, DM);
    make_map(enc, &tm_u, d_in[8], FF, DM);
    make_map(enc, &tm_d, d_in[9], DM, FF);
    cudaFuncSetAttribute(fused_attn_kernel, cudaFuncAttributeMaxDynamicSharedMemorySize, SMEM_BYTES);

    Scratch* sc = nullptr;
    cudaGetSymbolAddress((void**)&sc, g_scratch);

    cudaLaunchConfig_t cfg = {};
    cfg.gridDim = dim3(N_MAIN + N_MOE);
    cfg.blockDim = dim3(384);
    cfg.dynamicSmemBytes = SMEM_BYTES;
    cfg.stream = cudaStreamPerThread;
    cudaLaunchAttribute at[1];
    at[0].id = cudaLaunchAttributeClusterDimension;
    at[0].val.clusterDim.x = 2; at[0].val.clusterDim.y = 1; at[0].val.clusterDim.z = 1;
    cfg.attrs = at; cfg.numAttrs = 1;
    cudaLaunchKernelEx(&cfg, fused_attn_kernel, x, wr, out, sc, tm_x, tm_wq, tm_k, tm_v, tm_wo, tm_g, tm_u, tm_d);
}
```

```cpp
#include <cuda_runtime.h>
#include <cuda.h>
#include <cuda_bf16.h>
#include <stdint.h>

namespace {

constexpr int SEQ = 2048, DM = 640, NH = 32, DH = 128, FF = 1728, CAP = 8;
constexpr int NSLOT = 4;
constexpr int TILE_BYTES = 32768;
constexpr uint32_t RING_OFFSET = 1024;
constexpr int SMEM_BYTES = (NSLOT + 3) * TILE_BYTES + 416 + 1408 + 96;
constexpr int N_MAIN = 128, N_MOE = 4;

struct Scratch {
    uint4 part[16 * 8 * 9 * 2 * 4 * 128];
    uint4 gate[N_MAIN * 5 * 2 * 256];
    uint4 flag[16 * 8 * 32];
    uint4 qoff[16 * 4 * 2048];
    uint32_t flag_q[16];
    uint4 rare[N_MAIN * 17 * 256];
    float y[N_MOE * CAP * DM];
    uint2 routed[CAP * DM / 4];
    uint2 stat[SEQ];
    float r[SEQ];
    int idx[CAP];
    uint32_t flag_r[N_MOE], flag_y[N_MOE], flag_u[N_MOE];
    uint32_t epoch[N_MAIN + N_MOE];
};
__device__ Scratch g_scratch;

__device__ __forceinline__ uint32_t smem_u32(const void* p) { return (uint32_t)__cvta_generic_to_shared(p); }
__device__ __forceinline__ void mbar_init(uint32_t bar, uint32_t cnt) {
    asm volatile("mbarrier.init.shared::cta.b64 [%0], %1;" ::"r"(bar), "r"(cnt) : "memory");
}
__device__ __forceinline__ void mbar_wait(uint32_t bar, uint32_t parity) {
    asm volatile(
        "{\n.reg .pred p;\n"
        "LOOP:\n"
        "mbarrier.try_wait.parity.shared::cta.b64 p, [%0], %1;\n"
        "@!p bra.uni LOOP;\n"
        "DONE:\n}\n" ::"r"(bar), "r"(parity) : "memory");
}
__device__ __forceinline__ void mbar_wait_hot(uint32_t bar, uint32_t parity) {
    asm volatile(
        "{\n.reg .pred p;\n.reg .u32 c;\n"
        "mbarrier.test_wait.parity.shared::cta.b64 p, [%0], %1;\n"
        "@p bra.uni DONE;\n"
        "mov.u32 c, 0;\n"
        "LOOP:\n"
        "mbarrier.try_wait.parity.shared::cta.b64 p, [%0], %1;\n"
        "@p bra.uni DONE;\n"
        "add.u32 c, c, 1;\n"
        "setp.lt.u32 p, c, 2000000;\n"
        "@p bra.uni LOOP;\n"
        "trap;\n"
        "DONE:\n}\n" ::"r"(bar), "r"(parity) : "memory");
}
__device__ __forceinline__ void mbar_wait_bounded(uint32_t bar, uint32_t parity) {
    asm volatile(
        "{\n.reg .pred p;\n.reg .u32 c;\n"
        "mov.u32 c, 0;\n"
        "LOOP:\n"
        "mbarrier.try_wait.parity.shared::cta.b64 p, [%0], %1;\n"
        "@p bra.uni DONE;\n"
        "add.u32 c, c, 1;\n"
        "setp.lt.u32 p, c, 2000000;\n"
        "@p bra.uni LOOP;\n"
        "trap;\n"
        "DONE:\n}\n" ::"r"(bar), "r"(parity) : "memory");
}
__device__ __forceinline__ void mbar_wait_sleep(uint32_t bar, uint32_t parity) {
    asm volatile(
        "{\n.reg .pred p;\n.reg .u32 c;\n"
        "mov.u32 c, 0;\n"
        "LOOP:\n"
        "mbarrier.test_wait.parity.shared::cta.b64 p, [%0], %1;\n"
        "@p bra.uni DONE;\n"
        "nanosleep.u32 500;\n"
        "add.u32 c, c, 1;\n"
        "setp.lt.u32 p, c, 1000000;\n"
        "@p bra.uni LOOP;\n"
        "trap;\n"
        "DONE:\n}\n" ::"r"(bar), "r"(parity) : "memory");
}
__device__ __forceinline__ void mbar_expect_tx(uint32_t bar, uint32_t bytes) {
    asm volatile("mbarrier.arrive.expect_tx.shared::cta.b64 _, [%0], %1;" ::"r"(bar), "r"(bytes) : "memory");
}
template <int OFF>
__device__ __forceinline__ void release_at(uint32_t bar) {
    asm volatile(
        "{\n.reg .pred p;\n"
        "setp.ne.u32 p, %0, 0;\n"
        "@p mbarrier.arrive.shared::cluster.b64 _, [%0 + %1];\n}\n" ::"r"(bar), "n"(OFF) : "memory");
}
__device__ __forceinline__ void sched_fence(int zero) {
    asm volatile("{\n.reg .pred p;\n.reg .u32 c;\nsetp.ne.s32 p, %0, 0;\n@p mov.u32 c, %%clock;\n@p st.shared.u32 [%0], c;\n}\n" ::"r"(zero) : "memory");
}
__device__ __forceinline__ bool elect_one() {
    uint32_t r;
    asm volatile("{\n.reg .pred p;\nelect.sync _|p, 0xffffffff;\nselp.u32 %0, 1, 0, p;\n}\n" : "=r"(r));
    return r;
}
__device__ __forceinline__ uint32_t opaque(uint32_t v) {
    uint32_t r;
    asm volatile("mov.u32 %0, %1;" : "=r"(r) : "r"(v));
    return r;
}
__device__ __forceinline__ void tma_2d(uint32_t dst, const CUtensorMap* tm, uint32_t bar, int c0, int c1) {
    asm volatile(
        "cp.async.bulk.tensor.2d.shared::cluster.global.mbarrier::complete_tx::bytes [%0], [%1, {%3, %4}], [%2];"
        ::"r"(dst), "l"(tm), "r"(bar), "r"(c0), "r"(c1) : "memory");
}
__device__ __forceinline__ void tma_3d(uint32_t dst, const CUtensorMap* tm, uint32_t bar, int c0, int c1, int c2) {
    asm volatile(
        "cp.async.bulk.tensor.3d.shared::cluster.global.mbarrier::complete_tx::bytes [%0], [%1, {%3, %4, %5}], [%2];"
        ::"r"(dst), "l"(tm), "r"(bar), "r"(c0), "r"(c1), "r"(c2) : "memory");
}
__device__ __forceinline__ void tma_2d_mc(uint32_t dst, const CUtensorMap* tm, uint32_t bar, int c0, int c1) {
    asm volatile(
        "cp.async.bulk.tensor.2d.shared::cluster.global.mbarrier::complete_tx::bytes.multicast::cluster "
        "[%0], [%1, {%3, %4}], [%2], %5;"
        ::"r"(dst), "l"(tm), "r"(bar), "r"(c0), "r"(c1), "h"((uint16_t)3) : "memory");
}
__device__ __forceinline__ void tma_prefetch(const CUtensorMap* tm, int c0, int c1) {
    asm volatile("cp.async.bulk.prefetch.tensor.2d.L2.global [%0, {%1, %2}];" ::"l"(tm), "r"(c0), "r"(c1) : "memory");
}
__device__ __forceinline__ void mbar_arrive(uint32_t bar) {
    asm volatile("mbarrier.arrive.shared::cta.b64 _, [%0];" ::"r"(bar) : "memory");
}
__device__ __forceinline__ void flag_set(uint32_t* f, uint32_t v) {
    asm volatile("st.release.gpu.global.u32 [%0], %1;" ::"l"(f), "r"(v) : "memory");
}
template <int SLEEP_NS = 0>
__device__ __forceinline__ void flag_wait(const uint32_t* f, uint32_t v) {
    asm volatile(
        "{\n.reg .pred p;\n.reg .u32 c;\n"
        "LOOP:\n"
        "setp.ne.u32 p, %2, 0;\n"
        "@p nanosleep.u32 %2;\n"
        "ld.acquire.gpu.global.u32 c, [%0];\n"
        "setp.ne.u32 p, c, %1;\n"
        "@p bra LOOP;\n}\n" ::"l"(f), "r"(v), "n"(SLEEP_NS) : "memory");
}
template <int SLEEP_NS>
__device__ __forceinline__ void flag_wait_bounded(const uint32_t* f, uint32_t v) {
    asm volatile(
        "{\n.reg .pred p;\n.reg .u32 c, n;\n"
        "mov.u32 n, 0;\n"
        "LOOP:\n"
        "setp.ne.u32 p, %2, 0;\n"
        "@p nanosleep.u32 %2;\n"
        "ld.acquire.gpu.global.u32 c, [%0];\n"
        "setp.eq.u32 p, c, %1;\n"
        "@p bra DONE;\n"
        "add.u32 n, n, 1;\n"
        "setp.lt.u32 p, n, %3;\n"
        "@p bra LOOP;\n"
        "trap;\n"
        "DONE:\n}\n" ::"l"(f), "r"(v), "n"(SLEEP_NS), "n"(2000000) : "memory");
}
__device__ __forceinline__ void hmma(float (&d)[4], uint32_t a0, uint32_t a1, uint32_t a2, uint32_t a3, uint32_t b0, uint32_t b1) {
    asm volatile("mma.sync.aligned.m16n8k16.row.col.f32.bf16.bf16.f32 {%0,%1,%2,%3}, {%4,%5,%6,%7}, {%8,%9}, {%0,%1,%2,%3};"
                 : "+f"(d[0]), "+f"(d[1]), "+f"(d[2]), "+f"(d[3]) : "r"(a0), "r"(a1), "r"(a2), "r"(a3), "r"(b0), "r"(b1));
}
__device__ __forceinline__ void hmma8(float (&d)[4], uint32_t a0, uint32_t a1, uint32_t b0) {
    asm volatile("mma.sync.aligned.m16n8k8.row.col.f32.bf16.bf16.f32 {%0,%1,%2,%3}, {%4,%5}, {%6}, {%0,%1,%2,%3};"
                 : "+f"(d[0]), "+f"(d[1]), "+f"(d[2]), "+f"(d[3]) : "r"(a0), "r"(a1), "r"(b0));
}
__device__ __forceinline__ void ldsm4(uint32_t addr, uint32_t& a, uint32_t& b, uint32_t& c, uint32_t& d) {
    asm volatile("ldmatrix.sync.aligned.m8n8.x4.shared.b16 {%0, %1, %2, %3}, [%4];"
                 : "=r"(a), "=r"(b), "=r"(c), "=r"(d) : "r"(addr) : "memory");
}
__device__ __forceinline__ void stsm4(uint32_t addr, uint32_t a, uint32_t b, uint32_t c, uint32_t d) {
    asm volatile("stmatrix.sync.aligned.m8n8.x4.shared.b16 [%4], {%0, %1, %2, %3};"
                 ::"r"(a), "r"(b), "r"(c), "r"(d), "r"(addr) : "memory");
}
__device__ __forceinline__ uint32_t bf2_sub(uint32_t a, uint32_t b) {
    uint32_t d;
    asm("sub.rn.bf16x2 %0, %1, %2;" : "=r"(d) : "r"(a), "r"(b));
    return d;
}
template <int LUT>
__device__ __forceinline__ uint32_t lop3(uint32_t a, uint32_t b, uint32_t c) {
    uint32_t d;
    asm("lop3.b32 %0, %1, %2, %3, %4;" : "=r"(d) : "r"(a), "r"(b), "r"(c), "n"(LUT));
    return d;
}
__device__ __forceinline__ float rcp(float x) {
    float y;
    asm("rcp.approx.ftz.f32 %0, %1;" : "=f"(y) : "f"(x));
    return y;
}
__device__ __forceinline__ void bar_sync(int id) { asm volatile("bar.sync %0, 256;" ::"r"(id) : "memory"); }
__device__ __forceinline__ void bar_arrive(int id) { asm volatile("bar.arrive %0, 256;" ::"r"(id) : "memory"); }
__device__ __forceinline__ void wg_fence() { asm volatile("wgmma.fence.sync.aligned;" ::: "memory"); }
__device__ __forceinline__ void wg_commit() { asm volatile("wgmma.commit_group.sync.aligned;" ::: "memory"); }
template <int N> __device__ __forceinline__ void wg_wait() { asm volatile("wgmma.wait_group.sync.aligned %0;" ::"n"(N) : "memory"); }
template <int N>
__device__ __forceinline__ void pin(float (&d)[N]) {
#pragma unroll
    for (int i = 0; i < N; i++) asm volatile("" : "+f"(d[i])::"memory");
}
__device__ __forceinline__ uint32_t pack_bf16(float lo, float hi) {
    uint32_t r;
    asm("cvt.rn.bf16x2.f32 %0, %1, %2;" : "=r"(r) : "f"(hi), "f"(lo));
    return r;
}
__device__ __forceinline__ float bf_lo(uint32_t v) { return __uint_as_float(v << 16); }
__device__ __forceinline__ float bf_hi(uint32_t v) { return __uint_as_float(v & 0xffff0000u); }
__device__ __forceinline__ float bf_round(float v) { return __bfloat162float(__float2bfloat16_rn(v)); }
__device__ __forceinline__ float ex2(float x) {
    float y;
    asm("ex2.approx.ftz.f32 %0, %1;" : "=f"(y) : "f"(x));
    return y;
}
__device__ __forceinline__ void sts128(uint32_t addr, uint32_t a, uint32_t b, uint32_t c, uint32_t d) {
    asm volatile("st.shared.v4.b32 [%0], {%1, %2, %3, %4};" ::"r"(addr), "r"(a), "r"(b), "r"(c), "r"(d) : "memory");
}
__device__ __forceinline__ void lds128(uint32_t addr, uint32_t& a, uint32_t& b, uint32_t& c, uint32_t& d) {
    asm volatile("ld.shared.v4.b32 {%0, %1, %2, %3}, [%4];" : "=r"(a), "=r"(b), "=r"(c), "=r"(d) : "r"(addr) : "memory");
}

template <int OFF>
__device__ __forceinline__ void lds128_if(bool on, uint32_t addr, uint32_t& a, uint32_t& b, uint32_t& c, uint32_t& d) {
    asm volatile("{\n.reg .pred p;\nsetp.ne.u32 p, %5, 0;\n@p ld.shared.v4.b32 {%0, %1, %2, %3}, [%4 + %6];\n}\n"
                 : "+r"(a), "+r"(b), "+r"(c), "+r"(d) : "r"(addr), "r"((uint32_t)on), "n"(OFF) : "memory");
}

template <int TB>
__device__ __forceinline__ void wgmma_rs(float (&d)[64], uint32_t a0, uint32_t a1, uint32_t a2, uint32_t a3,
                                         uint64_t desc, int scale_d) {
    asm volatile(
        "{\n.reg .pred p;\nsetp.ne.b32 p, %69, 0;\n"
        "wgmma.mma_async.sync.aligned.m64n128k16.f32.bf16.bf16 "
        "{%0,%1,%2,%3,%4,%5,%6,%7,%8,%9,%10,%11,%12,%13,%14,%15,%16,%17,%18,%19,%20,%21,%22,%23,%24,%25,%26,%27,%28,%29,%30,%31,"
        "%32,%33,%34,%35,%36,%37,%38,%39,%40,%41,%42,%43,%44,%45,%46,%47,%48,%49,%50,%51,%52,%53,%54,%55,%56,%57,%58,%59,%60,%61,%62,%63},"
        "{%64,%65,%66,%67}, %68, p, 1, 1, %70;\n}\n"
        : "+f"(d[0]), "+f"(d[1]), "+f"(d[2]), "+f"(d[3]), "+f"(d[4]), "+f"(d[5]), "+f"(d[6]), "+f"(d[7]),
          "+f"(d[8]), "+f"(d[9]), "+f"(d[10]), "+f"(d[11]), "+f"(d[12]), "+f"(d[13]), "+f"(d[14]), "+f"(d[15]),
          "+f"(d[16]), "+f"(d[17]), "+f"(d[18]), "+f"(d[19]), "+f"(d[20]), "+f"(d[21]), "+f"(d[22]), "+f"(d[23]),
          "+f"(d[24]), "+f"(d[25]), "+f"(d[26]), "+f"(d[27]), "+f"(d[28]), "+f"(d[29]), "+f"(d[30]), "+f"(d[31]),
          "+f"(d[32]), "+f"(d[33]), "+f"(d[34]), "+f"(d[35]), "+f"(d[36]), "+f"(d[37]), "+f"(d[38]), "+f"(d[39]),
          "+f"(d[40]), "+f"(d[41]), "+f"(d[42]), "+f"(d[43]), "+f"(d[44]), "+f"(d[45]), "+f"(d[46]), "+f"(d[47]),
          "+f"(d[48]), "+f"(d[49]), "+f"(d[50]), "+f"(d[51]), "+f"(d[52]), "+f"(d[53]), "+f"(d[54]), "+f"(d[55]),
          "+f"(d[56]), "+f"(d[57]), "+f"(d[58]), "+f"(d[59]), "+f"(d[60]), "+f"(d[61]), "+f"(d[62]), "+f"(d[63])
        : "r"(a0), "r"(a1), "r"(a2), "r"(a3), "l"(desc), "r"(scale_d), "n"(TB));
}
__device__ __forceinline__ void wgmma_ss(float (&d)[64], uint64_t desc_a, uint64_t desc_b, int scale_d) {
    asm volatile(
        "{\n.reg .pred p;\nsetp.ne.b32 p, %66, 0;\n"
        "wgmma.mma_async.sync.aligned.m64n128k16.f32.bf16.bf16 "
        "{%0,%1,%2,%3,%4,%5,%6,%7,%8,%9,%10,%11,%12,%13,%14,%15,%16,%17,%18,%19,%20,%21,%22,%23,%24,%25,%26,%27,%28,%29,%30,%31,"
        "%32,%33,%34,%35,%36,%37,%38,%39,%40,%41,%42,%43,%44,%45,%46,%47,%48,%49,%50,%51,%52,%53,%54,%55,%56,%57,%58,%59,%60,%61,%62,%63},"
        "%64, %65, p, 1, 1, 0, 1;\n}\n"
        : "+f"(d[0]), "+f"(d[1]), "+f"(d[2]), "+f"(d[3]), "+f"(d[4]), "+f"(d[5]), "+f"(d[6]), "+f"(d[7]),
          "+f"(d[8]), "+f"(d[9]), "+f"(d[10]), "+f"(d[11]), "+f"(d[12]), "+f"(d[13]), "+f"(d[14]), "+f"(d[15]),
          "+f"(d[16]), "+f"(d[17]), "+f"(d[18]), "+f"(d[19]), "+f"(d[20]), "+f"(d[21]), "+f"(d[22]), "+f"(d[23]),
          "+f"(d[24]), "+f"(d[25]), "+f"(d[26]), "+f"(d[27]), "+f"(d[28]), "+f"(d[29]), "+f"(d[30]), "+f"(d[31]),
          "+f"(d[32]), "+f"(d[33]), "+f"(d[34]), "+f"(d[35]), "+f"(d[36]), "+f"(d[37]), "+f"(d[38]), "+f"(d[39]),
          "+f"(d[40]), "+f"(d[41]), "+f"(d[42]), "+f"(d[43]), "+f"(d[44]), "+f"(d[45]), "+f"(d[46]), "+f"(d[47]),
          "+f"(d[48]), "+f"(d[49]), "+f"(d[50]), "+f"(d[51]), "+f"(d[52]), "+f"(d[53]), "+f"(d[54]), "+f"(d[55]),
          "+f"(d[56]), "+f"(d[57]), "+f"(d[58]), "+f"(d[59]), "+f"(d[60]), "+f"(d[61]), "+f"(d[62]), "+f"(d[63])
        : "l"(desc_a), "l"(desc_b), "r"(scale_d));
}
__device__ __forceinline__ void wgmma_rs64(float (&d)[32], uint32_t a0, uint32_t a1, uint32_t a2, uint32_t a3,
                                           uint64_t desc, int scale_d) {
    asm volatile(
        "{\n.reg .pred p;\nsetp.ne.b32 p, %37, 0;\n"
        "wgmma.mma_async.sync.aligned.m64n64k16.f32.bf16.bf16 "
        "{%0,%1,%2,%3,%4,%5,%6,%7,%8,%9,%10,%11,%12,%13,%14,%15,%16,%17,%18,%19,%20,%21,%22,%23,%24,%25,%26,%27,%28,%29,%30,%31},"
        "{%32,%33,%34,%35}, %36, p, 1, 1, 1;\n}\n"
        : "+f"(d[0]), "+f"(d[1]), "+f"(d[2]), "+f"(d[3]), "+f"(d[4]), "+f"(d[5]), "+f"(d[6]), "+f"(d[7]),
          "+f"(d[8]), "+f"(d[9]), "+f"(d[10]), "+f"(d[11]), "+f"(d[12]), "+f"(d[13]), "+f"(d[14]), "+f"(d[15]),
          "+f"(d[16]), "+f"(d[17]), "+f"(d[18]), "+f"(d[19]), "+f"(d[20]), "+f"(d[21]), "+f"(d[22]), "+f"(d[23]),
          "+f"(d[24]), "+f"(d[25]), "+f"(d[26]), "+f"(d[27]), "+f"(d[28]), "+f"(d[29]), "+f"(d[30]), "+f"(d[31])
        : "r"(a0), "r"(a1), "r"(a2), "r"(a3), "l"(desc), "r"(scale_d));
}
__device__ __forceinline__ void wgmma_ss64(float (&d)[32], uint64_t desc_a, uint64_t desc_b, int scale_d) {
    asm volatile(
        "{\n.reg .pred p;\nsetp.ne.b32 p, %34, 0;\n"
        "wgmma.mma_async.sync.aligned.m64n64k16.f32.bf16.bf16 "
        "{%0,%1,%2,%3,%4,%5,%6,%7,%8,%9,%10,%11,%12,%13,%14,%15,%16,%17,%18,%19,%20,%21,%22,%23,%24,%25,%26,%27,%28,%29,%30,%31},"
        "%32, %33, p, 1, 1, 0, 1;\n}\n"
        : "+f"(d[0]), "+f"(d[1]), "+f"(d[2]), "+f"(d[3]), "+f"(d[4]), "+f"(d[5]), "+f"(d[6]), "+f"(d[7]),
          "+f"(d[8]), "+f"(d[9]), "+f"(d[10]), "+f"(d[11]), "+f"(d[12]), "+f"(d[13]), "+f"(d[14]), "+f"(d[15]),
          "+f"(d[16]), "+f"(d[17]), "+f"(d[18]), "+f"(d[19]), "+f"(d[20]), "+f"(d[21]), "+f"(d[22]), "+f"(d[23]),
          "+f"(d[24]), "+f"(d[25]), "+f"(d[26]), "+f"(d[27]), "+f"(d[28]), "+f"(d[29]), "+f"(d[30]), "+f"(d[31])
        : "l"(desc_a), "l"(desc_b), "r"(scale_d));
}
__device__ __forceinline__ uint64_t desc_kmajor(uint32_t tile16, int ks) {
    uint32_t lo = tile16 + ((ks >> 2) * 1024 + (ks & 3) * 2 + (1u << 16));
    return ((uint64_t)0x40000040u << 32) | lo;
}
__device__ __forceinline__ uint64_t desc_nmajor(uint32_t tile16, int ks) {
    uint32_t lo = tile16 + (ks * 128 + (1024u << 16));
    return ((uint64_t)0x40000040u << 32) | lo;
}
template <int TB>
__device__ __forceinline__ void mma_tile(float (&d)[64], const uint32_t* a, uint32_t tile16, int accumulate) {
#pragma unroll
    for (int ks = 0; ks < 8; ks++)
        wgmma_rs<TB>(d, a[4 * ks], a[4 * ks + 1], a[4 * ks + 2], a[4 * ks + 3],
                     TB ? desc_nmajor(tile16, ks) : desc_kmajor(tile16, ks), ks == 0 ? accumulate : 1);
    wg_commit();
}

template <int V> struct cint { static constexpr int value = V; };
#define GPF 126
#define XN 2
#define FINK 3
#define G4 0
#define QAT 110
#define FSPLIT 2
#define SPLIT 32
#define SPLITO 24

#define TRM(i)
#define TR(i)
#define TG(i)
#define PT(k)
#define TS(k)
#define TA(k)
#define TL(k)
#define TF(i)
#define TH(w, i)
#define TC(k)

__device__ __forceinline__ float silu_f(float v) { return v * rcp(1.f + ex2(v * -1.4426950408889634f)); }

__device__ __forceinline__ float inv_den(float var) {
    float r;
    asm("sqrt.approx.f32 %0, %1;" : "=f"(r) : "f"(bf_round(bf_round(var) + 1e-5f)));
    return rcp(bf_round(r));
}
__device__ __forceinline__ uint32_t normalise(uint32_t x2, uint32_t mm, float id) {
    const uint32_t d = bf2_sub(x2, mm);
    return pack_bf16(bf_lo(d) * id, bf_hi(d) * id);
}

__device__ __forceinline__ uint32_t silu2(uint32_t u) { return pack_bf16(silu_f(bf_lo(u)), silu_f(bf_hi(u))); }

__device__ __forceinline__ uint32_t silu2_ln(uint32_t u) {
    const float a = bf_lo(u), b = bf_hi(u);
    const float da = 1.f + ex2(a * -1.4426950408889634f), db = 1.f + ex2(b * -1.4426950408889634f);
    const float r = rcp(da * db);
    return pack_bf16(a * db * r, b * da * r);
}

__device__ __forceinline__ uint2 load_stat(Scratch* sc, int row) {
    uint2 v;
    asm volatile("ld.relaxed.gpu.global.v2.u32 {%0, %1}, [%2];" : "=r"(v.x), "=r"(v.y) : "l"(sc->stat + row) : "memory");
    return make_uint2(__byte_perm(v.x, 0, 0x1010), v.y);
}

constexpr int FSLOT = 6;
__device__ __forceinline__ void ffn_role(Scratch* sc, uint32_t ring, uint32_t ffull, uint32_t fempty, uint32_t alldone, int e, uint32_t ep, int warp,
                                         const __nv_bfloat16* __restrict__ x) {
    const uint32_t xs = ring + FSLOT * TILE_BYTES, hs = xs + 10 * 1024, cand = hs + 8 * 1024, sig = cand + 256;
    int tid;
    asm volatile("mov.u32 %0, %%tid.x;" : "=r"(tid));
    const int lane = tid & 31;
    [[maybe_unused]] const int wg = warp >> 2;
    const int nb = e == N_MOE - 1 ? 6 : 7, nkt = (nb + 1) >> 1;
    auto sync = [] { asm volatile("bar.sync 3, 256;" ::: "memory"); };
    if (tid < N_MOE) flag_wait(sc->flag_r + tid, ep);
    sync();
    TR(6);

    {
        uint32_t key[8];
#pragma unroll
        for (int i = 0; i < 8; i++) {
            const int j = warp * 256 + i * 32 + lane;
            const uint32_t u = __float_as_uint(__ldcg(sc->r + j) + 0.f);
            key[i] = (((u & 0x80000000u) ? ~u : (u | 0x80000000u)) & 0xffff0000u) | (uint32_t)(SEQ - j);
        }
#pragma unroll 1
        for (int k = 0; k < CAP; k++) {
            uint32_t b = key[0];
#pragma unroll
            for (int i = 1; i < 8; i++) b = max(b, key[i]);
            b = __reduce_max_sync(0xffffffffu, b);
#pragma unroll
            for (int i = 0; i < 8; i++) if (key[i] == b) key[i] = 0;
            if (lane == 0) asm volatile("st.shared.u32 [%0], %1;" ::"r"(cand + (warp * 8 + k) * 4), "r"(b) : "memory");
        }
    }
    sync();
    {
        uint32_t k0, k1, b = 0;
        asm volatile("ld.shared.v2.u32 {%0, %1}, [%2];" : "=r"(k0), "=r"(k1) : "r"(cand + lane * 8));
#pragma unroll 1
        for (int k = 0; k <= warp; k++) {
            b = __reduce_max_sync(0xffffffffu, max(k0, k1));
            if (k0 == b) k0 = 0;
            if (k1 == b) k1 = 0;
        }
        const int row = SEQ - (int)(b & 0xffffu);
        const uint2 st = load_stat(sc, row);
        uint4 v[3];
#pragma unroll
        for (int k = 0; k < 3; k++) v[k] = __ldg((const uint4*)(x + (size_t)row * DM) + min(lane + 32 * k, DM / 8 - 1));
#pragma unroll
        for (int k = 0; k < 3; k++) {
            const int i = lane + 32 * k;
            const float id = __uint_as_float(st.y);
            if (i < DM / 8)
                sts128(xs + (i >> 3) * 1024 + warp * 128 + (((i & 7) ^ warp) << 4), normalise(v[k].x, st.x, id), normalise(v[k].y, st.x, id),
                       normalise(v[k].z, st.x, id), normalise(v[k].w, st.x, id));
        }
        asm volatile("fence.proxy.async.shared::cta;" ::: "memory");
        if (lane == 0) {
            const float sg = bf_round(rcp(1.f + __expf(-__ldcg(sc->r + row))));
            asm volatile("st.shared.v2.b32 [%0], {%1, %2};" ::"r"(sig + warp * 8), "f"(sg), "r"(row) : "memory");
        }
    }
    sync();
    TR(7);

    {
        float acc[64];
        const int g = lane >> 2, t4 = lane & 3;
        auto block = [&](uint32_t a, uint32_t n, int step, int halves) {
#pragma unroll 1
            for (int i = 0; i < halves; i += 2, n += step) {
                const uint32_t s = n % FSLOT;
                mbar_wait(ffull + 8 * s, (n / FSLOT) & 1);
                const uint32_t a16 = (((a + i * 1024) & 0x3FFFFu) >> 4) | (1u << 16);
                const uint32_t b16 = ((ring + s * TILE_BYTES) & 0x3FFFFu) >> 4;
                auto mmas = [&](auto n_c) {
                    wg_fence();
#pragma unroll
                    for (int ks = 0; ks < decltype(n_c)::value; ks++)
                        wgmma_ss(acc, ((uint64_t)0x40000000u << 32) | (a16 + (ks >> 2) * 64 + (ks & 3) * 2), desc_nmajor(b16, ks), ks || i);
                    wg_commit();
                    wg_wait<0>();
                };
                if (i + 1 < halves) mmas(cint<8>());
                else mmas(cint<4>());
                if (lane == 0) mbar_arrive(fempty + 8 * s);
            }
            pin(acc);
        };
#pragma unroll 1
        for (int o = warp >> 2; o < nb; o += 2) {
            const bool pair = (o | 1) < nb;
            block(xs, 5 * (o & ~1) + (pair ? o & 1 : 0), pair ? 2 : 1, 10);
#pragma unroll
            for (int j = 0; j < 8; j++) {
                uint32_t h = pack_bf16(silu_f(bf_round(acc[4 * j])), silu_f(bf_round(acc[4 * j + 1])));
                asm("mul.rn.bf16x2 %0, %0, %1;" : "+r"(h) : "r"(pack_bf16(acc[32 + 4 * j], acc[33 + 4 * j])));
                asm volatile("st.shared.u32 [%0], %1;" ::"r"(hs + o * 1024 + g * 128 + ((j ^ g) << 4) + t4 * 4), "r"(h) : "memory");
            }
        }
        asm volatile("fence.proxy.async.shared::cta;" ::: "memory");
        sync();
        TR(8);
#pragma unroll 1
        for (int o = warp >> 2; o < 5; o += 2) {
            block(hs, 5 * nb + (o & ~1) * nkt + (o & 1), o < 4 ? 2 : 1, nb);
            if ((warp & 3) == 0) {
#pragma unroll
                for (int j = 0; j < 16; j++)
                    *(float2*)(sc->y + (e * CAP + g) * DM + o * 128 + j * 8 + t4 * 2) = make_float2(acc[4 * j], acc[4 * j + 1]);
            }
        }
    }
    sync();
    TR(9);
    if (tid == 0) flag_set(sc->flag_y + e, ep);
    if (tid < N_MOE) flag_wait(sc->flag_y + tid, ep);
    sync();
    if (lane == 0) mbar_arrive(alldone);
#pragma unroll 1
    for (int t = tid; t < 320; t += 256) {
        const int i = 2 * e * DM + t * 4;
        float4 y = __ldcg((const float4*)(sc->y + i));
#pragma unroll
        for (int j = 1; j < N_MOE; j++) {
            const float4 z = __ldcg((const float4*)(sc->y + j * CAP * DM + i));
            y.x += z.x; y.y += z.y; y.z += z.z; y.w += z.w;
        }
        float sg;
        int row;
        asm volatile("ld.shared.v2.b32 {%0, %1}, [%2];" : "=f"(sg), "=r"(row) : "r"(sig + (i / DM) * 8));
        const int o4 = (row * DM + i % DM) / 4;
        const uint2 v = __ldg((const uint2*)x + o4), st = load_stat(sc, row);
        uint32_t u0 = normalise(v.x, st.x, __uint_as_float(st.y)), u1 = normalise(v.y, st.x, __uint_as_float(st.y));
        asm("add.rn.bf16x2 %0, %0, %1;" : "+r"(u0) : "r"(pack_bf16(bf_round(y.x) * sg, bf_round(y.y) * sg)));
        asm("add.rn.bf16x2 %0, %0, %1;" : "+r"(u1) : "r"(pack_bf16(bf_round(y.z) * sg, bf_round(y.w) * sg)));
        sc->routed[i / 4] = make_uint2(silu2(u0), silu2(u1));
        if (i % DM == 0) sc->idx[i / DM] = row;
    }
    sync();
    TR(10);
    if (tid == 0) flag_set(sc->flag_u + e, ep);
}

__global__ void __launch_bounds__(384, 1)
fused_attn_kernel(const __nv_bfloat16* __restrict__ x, const __nv_bfloat16* __restrict__ wr,
                  __nv_bfloat16* __restrict__ out, Scratch* sc,
                  const __grid_constant__ CUtensorMap tm_x, const __grid_constant__ CUtensorMap tm_wq,
                  const __grid_constant__ CUtensorMap tm_k, const __grid_constant__ CUtensorMap tm_v,
                  const __grid_constant__ CUtensorMap tm_wo, const __grid_constant__ CUtensorMap tm_g,
                  const __grid_constant__ CUtensorMap tm_u, const __grid_constant__ CUtensorMap tm_d) {
    PT(0);
    extern __shared__ __align__(16) uint8_t smem_raw[];
    const uint32_t ring = smem_u32(smem_raw);
    const uint32_t stash = ring + NSLOT * TILE_BYTES;
    const uint32_t bars = stash + 3 * TILE_BYTES;
    const uint32_t full = bars, empty = bars + 32;
    const uint32_t xfull = bars + 64;
    const uint32_t rfull = bars + 144;
    const uint32_t rdone = bars + 288;
    const uint32_t vacant = bars + 336, routed = bars + 344, xgfull = bars + 352, gated = bars + 360;
    const uint32_t soon = bars + 376, qfull = bars + 384, epv = bars + 392, alldone = bars + 400;
    const uint32_t epoch = bars + 368;
    [[maybe_unused]] const uint32_t trbuf = bars + 416;
    const uint32_t ffull = rfull, fempty = rfull + 8 * FSLOT, qdone = rdone, h1done = rdone + 32, wperm = trbuf;

    const int warp = __shfl_sync(0xffffffffu, threadIdx.x >> 5, 0), wg = warp >> 2;
    const int rank = blockIdx.x & 1;
    const int cl = blockIdx.x >> 1;
    const int r7 = ((cl - 36) * 37) >> 8;
    const int qp = cl < 36 ? (cl < 4 ? 0 : (cl - 4) & 7) : cl - 35 - 7 * r7;
    const int grp = cl < 4 ? cl + 4 : cl < 36 ? (cl - 4) >> 3 : r7 + 4;
    const bool helper = blockIdx.x >= N_MAIN;
    const int qt = helper ? (blockIdx.x - N_MAIN) * 4 : qp * 2 + rank;

    auto load_x = [&](int w, int i, int tile) {
        const uint32_t bar = xfull + (w * 5 + i) * 8;
        mbar_expect_tx(bar, 16384);
        tma_3d(ring + (i == 4 ? 2 : 3 + i) * TILE_BYTES + w * 16384, &tm_x, bar, 0, tile * 128 + w * 64, i == 0 ? 8 : 2 * i - 2);
    };
    if (warp == 4) {
        if (elect_one()) {
#pragma unroll
            for (int i = 0; i < 10; i++) mbar_init(xfull + 8 * i, 1);
#pragma unroll
            for (int i = 0; i < XN; i++) load_x(i & 1, i >> 1, qt);
            asm volatile("fence.mbarrier_init.release.cluster;" ::: "memory");
        }
        __syncwarp();
    }
    PT(6);
    if ((ring & 0xFFFFFFu) != RING_OFFSET) return;
    PT(7);
    if (warp >= 5 && elect_one()) {
        if (warp == 5) {
#pragma unroll
            for (int i = 0; i < NSLOT; i++) { mbar_init(full + 8 * i, 1); mbar_init(empty + 8 * i, 16); }
            mbar_arrive(full + 16);
            mbar_arrive(full + 24);
        } else if (warp == 6) {
#pragma unroll
            for (int i = 0; i < 6; i++) mbar_init(rdone + 8 * i, helper ? 8 : 4);
        } else if (warp == 7) {
            mbar_init(vacant, 8); mbar_init(routed, 32); mbar_init(xgfull, 1); mbar_init(gated, 8); mbar_init(soon, 1);
            mbar_init(qfull, 1); mbar_init(epv, 1); mbar_init(alldone, 8);
        } else if (warp == 8) {
            asm volatile("prefetch.tensormap [%0];" ::"l"(&tm_wq) : "memory");
        } else {
#pragma unroll
            for (int i = 0; i < 6; i++) mbar_init(rfull + ((warp - 9) * 6 + i) * 8, helper && warp == 10 ? 4 : 1);
        }
        asm volatile("fence.mbarrier_init.release.cluster;" ::: "memory");
    }
    __syncwarp();
    PT(1);
    asm volatile("barrier.cluster.arrive.relaxed.aligned;" ::: "memory");
    if (warp == 4) {
        if (elect_one()) {
#pragma unroll
            for (int i = XN; i < 10; i++) load_x(i & 1, i >> 1, qt);
        }
        __syncwarp();
    }

    if (wg == 2) {
        asm volatile("setmaxnreg.dec.sync.aligned.u32 24;");
        asm volatile("barrier.cluster.wait.aligned;" ::: "memory");
        uint32_t lane;
        asm volatile("mov.u32 %0, %%laneid;" : "=r"(lane));
        PT(2);
        if (warp == 8 && helper) {
          if (elect_one()) {
#pragma unroll 1
            for (int t = 0; t < 4; t++) {
#pragma unroll 1
                for (int i = 0; i < 20; i++) {
                    const int s = i % 3;
                    mbar_wait(empty + 8 * s, ((t + (i + 1) / 3) & 1) ^ 1);
                    mbar_expect_tx(full + 8 * s, TILE_BYTES);
                    tma_2d_mc(ring + s * TILE_BYTES + rank * 16384, &tm_wq, full + 8 * s, (((i / 5) * 2 + rank) * 4 + 3) * 128 + 64,
                              ((i + 4) % 5) * 128);
                    if (t == 0 && i == 2) {
                        asm volatile("nanosleep.u32 1500;");
#pragma unroll 1
                        for (int k = 3 + ((blockIdx.x >> 1) & 1); k < 20; k += 2) tma_prefetch(&tm_wq, (((k / 5) * 2 + rank) * 4 + 3) * 128 + 64, ((k + 4) % 5) * 128);
                    }
                    if (i == 2 && t < 3) {
#pragma unroll 1
                        for (int k = 2; k < 8; k++) load_x(k & 1, k >> 1, qt + t + 1);
                    }
                    if (i == 18 && t < 3) {
                        mbar_wait(empty + 24, t & 1);
                        load_x(0, 0, qt + t + 1); load_x(1, 0, qt + t + 1);
                    }
                }
                if (t < 3) {
                    mbar_wait(empty + 16, t & 1);
                    mbar_arrive(full + 16);
                    load_x(0, 4, qt + t + 1); load_x(1, 4, qt + t + 1);
                }
            }
            const int e = blockIdx.x - N_MAIN, nb = e == N_MOE - 1 ? 6 : 7, nkt = (nb + 1) >> 1;
            mbar_wait(h1done, 0);
            uint32_t s = 0, ph = 1;
#pragma unroll 1
            for (int o0 = 0, w; o0 < nb + 5; o0 += w) {
                const bool up = o0 < nb;
                w = o0 + 1 < (up ? nb : nb + 5) ? 2 : 1;
#pragma unroll 1
                for (int k = 0; k < (up ? 5 : nkt) * w; k++) {
                    const int o = o0 + (k & (w - 1)), i = k >> (w - 1);
                    mbar_wait(fempty + 8 * s, ph);
                    mbar_expect_tx(ffull + 8 * s, TILE_BYTES);
                    const int c0 = up ? (e * 7 + o) * 64 : (o - nb) * 128, c1 = (up ? 0 : e * 448) + i * 128;
                    tma_2d(ring + s * TILE_BYTES, up ? &tm_g : &tm_d, ffull + 8 * s, c0, c1);
                    tma_2d(ring + s * TILE_BYTES + 16384, up ? &tm_u : &tm_d, ffull + 8 * s, up ? c0 : c0 + 64, c1);
                    if (++s == FSLOT) { s = 0; ph ^= 1; }
                }
            }
          }
        } else if (warp == 8) {
          if (elect_one()) {
            PT(3);
            auto coords = [&](int i, const CUtensorMap*& tm, int& c0, int& c1) {
                c0 = rank * 64;
                if (i < 20) {
                    const int ps = i / 5;
                    tm = &tm_wq; c1 = (i % 5 < 3 ? i % 5 : 7 - i % 5) * 128;
                    if (ps == 1) {
                        c0 = 0;
                        c1 = (i == 5 ? rank : i == 6 ? 2 : 4 - rank) * 128;
                    }
                    c0 += (grp * 4 + (ps < 2 ? 2 + ps : 3 - ps)) * 128;
                } else if (i < 148) {
                    const int u = i - 20;
                    const bool isk = (u == 0) || ((u & 1) && u != 127);
                    const int b = isk ? (u + 1) >> 1 : (u == 127 ? 63 : (u >> 1) - 1);
                    tm = isk ? &tm_k : &tm_v; c1 = (grp * 64 + b) * 128;
                } else {
                    tm = &tm_wo; c0 = (i < 152 ? ((i - 132) >> 1) ^ (grp >> 2) : (grp + ((i - 150) >> 1)) & 7) * 64; c1 = (grp * 4 + (i & 1) * 2 + rank) * 128;
                }
            };
#pragma unroll 1
            for (int i = 0; i < 168; i++) {
                const CUtensorMap* tm;
                int c0, c1;
                if (i == 8) i = 10;
                const int a = i < 8 ? i : i - 2;
                const int s = i < 20 ? a % 3 : (i & 3);
                const uint32_t ph = i < 20 ? ((a + 1) / 3) & 1 : ((i >> 2) & 1) ^ (s < 2);
                coords(i, tm, c0, c1);
                if (i == QAT) mbar_wait(qfull, 0);
                mbar_wait(empty + 8 * s, ph ^ 1);
                if (i == 6) {
                    mbar_expect_tx(full + 8 * s, TILE_BYTES / 2);
                    if (rank == 0) tma_2d_mc(ring + s * TILE_BYTES, tm, full + 8 * s, c0, c1);
                } else {
                    mbar_expect_tx(full + 8 * s, TILE_BYTES);
                    tma_2d_mc(ring + s * TILE_BYTES + rank * 16384, tm, full + 8 * s, c0, c1);
                }
                if (i == 140) mbar_arrive(soon);
                if (i >= 163 && i < 167) {
                    if (i == 163) {
                        TL(0);
                        mbar_wait(routed, 0);
                        asm volatile("fence.proxy.async.global;" ::: "memory");
                        TL(1);
                        mbar_expect_tx(xgfull, TILE_BYTES);
                    }
                    asm volatile("cp.async.bulk.shared::cluster.global.mbarrier::complete_tx::bytes [%0], [%1], 8192, [%2];"
                                 ::"r"(stash + 3 * 16384 + (i - 163) * 8192), "l"(sc->gate + blockIdx.x * 2560 + (i - 163) * 512), "r"(xgfull) : "memory");
                }
                if (i == 12) asm volatile("prefetch.tensormap [%0];\nprefetch.tensormap [%1];" ::"l"(&tm_k), "l"(&tm_v) : "memory");
                if (i == 140) asm volatile("prefetch.tensormap [%0];" ::"l"(&tm_wo) : "memory");
                if (i >= GPF && i < GPF + 10)
                    asm volatile("cp.async.bulk.prefetch.L2.global [%0], 4096;" ::"l"(sc->gate + blockIdx.x * 2560 + (i - GPF) * 256) : "memory");
                const int j = i < 2 ? 2 + i : i == 2 ? 4 + ((qp - 4) & 7) : i + 9;
                if (j < 168 && (j & 7) == qp && (j & ~1) != 8) {
                    coords(j, tm, c0, c1);
                    tma_prefetch(tm, c0, c1);
                }
            }
            sc->epoch[blockIdx.x] += 1;
          }
        } else if (warp == 9) {
            const uint32_t ep = sc->epoch[blockIdx.x] + 1;
            if (helper) {
#pragma unroll 1
                for (int t = 0; t < 4; t++) {
                    if (t == 3) {
                        mbar_wait_sleep(qdone + 40, 0);
                        if (lane == 0) flag_set(sc->flag_r + (blockIdx.x - N_MAIN), ep);
                    }
                    mbar_wait_sleep(qdone + 8 * t, 0);
                    if (lane == 0) flag_set(sc->flag_q + qt + t, ep);
                }
                if (lane == 0) sc->epoch[blockIdx.x] = ep;
            } else {
                mbar_wait_sleep(gated, 0);
                flag_wait_bounded<300>(sc->flag_q + qt, ep);
                asm volatile("fence.proxy.async.global;" ::: "memory");
                if (lane == 0) mbar_expect_tx(qfull, 16384);
                __syncwarp();
                if (lane < 8)
                    asm volatile("cp.async.bulk.shared::cluster.global.mbarrier::complete_tx::bytes [%0], [%1], 2048, [%2];"
                                 ::"r"(stash + 2 * TILE_BYTES + lane * 4096 + 2048),
                                   "l"(sc->qoff + ((qt * 4 + (grp >> 1)) * 8 + lane) * 256 + (grp & 1) * 128), "r"(qfull) : "memory");
            }
            mbar_wait_bounded(alldone, 0);
        } else if (helper) {
        } else if (warp == 10) {
            const uint32_t ep = sc->epoch[blockIdx.x] + 1;
            if (lane == 0) {
                asm volatile("st.shared.u32 [%0], %1;" ::"r"(epoch), "r"(ep) : "memory");
                mbar_arrive(epv);
            }
            mbar_wait_sleep(gated, 0);
            flag_wait<400>(sc->flag_u + (lane & 3), ep);
            __syncwarp();
            const int rrow = __ldcg(sc->idx + (lane & 7));
            uint32_t hit = __ballot_sync(0xffffffffu, lane < 8 && (rrow >> 7) == qt);
            while (hit) {
                const int k = __ffs(hit) - 1, row = __shfl_sync(0xffffffffu, rrow, k);
                hit &= hit - 1;
#pragma unroll 1
                for (int i = lane; i < 40; i += 32) {
                    const int th = ((row >> 4) & 7) * 32 + (row & 7) * 4 + (i & 3);
                    ((uint32_t*)sc->gate)[(((blockIdx.x * 5 + (i >> 3)) * 2 + 1) * 256 + th) * 4 + ((i >> 1) & 2) + ((row >> 3) & 1)] =
                        __ldcg((const uint32_t*)sc->routed + k * (DM / 2) + (i < 32 ? grp * 32 + i : 224 + grp * 8 + i));
                }
            }
            mbar_arrive(routed);
        } else if (warp == 11) {
            const uint32_t ep = sc->epoch[blockIdx.x] + 1;
            const uint32_t unit = lane < 16 ? lane >> 3 : (lane >> 1) - 6;
            const uint32_t ofs = (lane & 1) * 8192 + (lane < 16 ? ((lane >> 1) & 3) * 2048 : 0);
            if (lane < 18) mbar_expect_tx(rfull + 8 * lane, 8192);
            mbar_wait_sleep(soon, 0);
            uint32_t done = lane >= 30;
            do {
                if (!done) {
                    uint4 v;
                    asm volatile("ld.relaxed.gpu.global.v4.u32 {%0, %1, %2, %3}, [%4];" : "=r"(v.x), "=r"(v.y), "=r"(v.z), "=r"(v.w)
                                 : "l"(sc->flag + (qt * 8 + grp) * 32 + lane) : "memory");
                    uint32_t ok = v.x == ep && v.y == ep && v.z == ep && v.w == ep;
                    if (ok)
                        asm volatile("{\n.reg .pred p;\nmbarrier.test_wait.parity.shared::cta.b64 p, [%1], 0;\nselp.u32 %0, 1, 0, p;\n}\n"
                                     : "=r"(ok) : "r"(unit >= 6 ? rdone + (lane - 24) * 8 : vacant) : "memory");
                    done = ok;
                    if (ok)
                        asm volatile("cp.async.bulk.shared::cluster.global.mbarrier::complete_tx::bytes [%0], [%1], %2, [%3];"
                                     ::"r"(stash + (unit >= 6 ? unit - 6 : unit) * 16384 + ofs),
                                       "l"((const char*)sc->part + ((qt * 8 + grp) * 9 + unit) * 16384 + ofs), "r"(lane < 16 ? 2048 : 8192),
                                       "r"(rfull + 16 * unit + 8 * (lane & 1)) : "memory");
                }
            } while (!__all_sync(0xffffffffu, done));
        }
    } else {
        asm volatile("setmaxnreg.inc.sync.aligned.u32 240;");
        const uint32_t lane = threadIdx.x & 31;
        PT(2);
        asm volatile("barrier.cluster.wait.aligned;" ::: "memory");
        PT(3);
        const int my_bar = 1 + wg, other_bar = 2 - wg;
        const uint32_t my_stash = stash + warp * 4096 + lane * 16;
        constexpr uint32_t T16 = TILE_BYTES / 16;
        constexpr uint32_t ring16 = RING_OFFSET >> 4;
        uint32_t rel = 0;
        if (lane < 2)
            asm("mapa.shared::cluster.u32 %0, %1, %2;" : "=r"(rel) : "r"(empty), "r"(lane));
        rel = opaque(rel);

        const int zero = gridDim.y - 1;
        PT(4);

        uint32_t q[32];
        float acc[64];
        float wsum;
        uint32_t ep_tag;
        uint2 st0, st1;
        auto project = [&](auto helper_c, int job) {
            constexpr bool HELPER = decltype(helper_c)::value;
            float (&acc32)[32] = *reinterpret_cast<float (*)[32]>(&acc[0]);
            const int tile = qt + job;
            uint32_t lane = threadIdx.x & 31;
            if (HELPER) asm volatile("mov.u32 %0, %%laneid;" : "=r"(lane));
            uint32_t xa[128];
            const uint32_t lm_off = wg * 16384 + ((warp & 3) * 16 + (lane & 15)) * 128 + (((lane >> 4) ^ (lane & 7)) << 4);
            float sm[4][4] = {}, sq[4][4] = {};
            constexpr uint32_t ONES = 0x3f803f80u;
            constexpr float SC = 0.08838834764831845f * 1.4426950408889634f;
            auto squares = [&](const uint32_t* a) {
#pragma unroll
                for (int r = 0; r < 4; r++) hmma8(sq[r], a[r & 2], a[(r & 2) + 1], a[r]);
            };
            const int row = tile * 128 + warp * 16 + (lane >> 2);
            auto load_stats = [&](int t) {
                asm volatile("ld.relaxed.gpu.global.v2.u32 {%0, %1}, [%4];\nld.relaxed.gpu.global.v2.u32 {%2, %3}, [%4 + 64];"
                             : "=r"(st0.x), "=r"(st0.y), "=r"(st1.x), "=r"(st1.y) : "l"(sc->stat + t * 128 + warp * 16 + (lane >> 2)) : "memory");
            };
            uint32_t mm0, mm1;
            float rd0, rd1;
            if (HELPER && job == 0) load_stats(tile);
#pragma unroll
            for (int i = 0; i < 5; i++) {
                mbar_wait(xfull + (wg * 5 + i) * 8, HELPER ? job & 1 : 0);
                if (i == 0) PT(5);
                if (HELPER && i == 0) TR(20 + job * 8);
                if (HELPER && i == 4) TR(20 + job * 8 + 7);
                if (HELPER && job == 1) TR(110 + i);
                const uint32_t base = ring + (i == 4 ? 2 : 3 + i) * TILE_BYTES + lm_off;
                uint32_t* a = xa + (i == 0 ? 96 : 32 * (i - 1));
#pragma unroll
                for (int ks = 0; ks < 8; ks++)
                    ldsm4((base ^ ((ks & 3) << 5)) + (ks >> 2) * 8192, a[4 * ks], a[4 * ks + 1], a[4 * ks + 2], a[4 * ks + 3]);
                if (i == 4) PT(9);
                uint32_t wb[16];
#pragma unroll
                for (int ks = 0; ks < 8; ks++) {
                    wb[2 * ks] = ONES; wb[2 * ks + 1] = ONES;
                    if (HELPER)
                        asm volatile("ld.shared.v2.u32 {%0, %1}, [%2];" : "=r"(wb[2 * ks]), "=r"(wb[2 * ks + 1]) : "r"(wperm + (lane & 3) * 8 + ((i == 0 ? 32 : 8 * i - 8) + ks) * 32));
                }
#pragma unroll
                for (int ks = 0; ks < 8; ks++) {
                    hmma(sm[ks & 3], a[4 * ks], a[4 * ks + 1], a[4 * ks + 2], a[4 * ks + 3], wb[2 * ks], wb[2 * ks + 1]);
                    if (!HELPER && i < 4) squares(a + 4 * ks);
                }
                if (HELPER && i == 0) {
                    while (__any_sync(0xffffffffu, ((st0.x ^ ep_tag) | (st1.x ^ ep_tag)) >> 16)) load_stats(tile);
                    mm0 = __byte_perm(st0.x, 0, 0x1010); mm1 = __byte_perm(st1.x, 0, 0x1010);
#pragma unroll
                    for (int ks = 0; ks < 8; ks++)
                        stsm4((base ^ ((ks & 3) << 5)) + (ks >> 2) * 8192, bf2_sub(a[4 * ks], mm0), bf2_sub(a[4 * ks + 1], mm1),
                              bf2_sub(a[4 * ks + 2], mm0), bf2_sub(a[4 * ks + 3], mm1));
                    asm volatile("fence.proxy.async.shared::cta;" ::: "memory");
                }
            }
            release_at<16>(rel);
            sched_fence(zero);
            const float m0 = ((sm[0][0] + sm[1][0]) + (sm[2][0] + sm[3][0])) * (HELPER ? 1.f : 1.f / DM);
            const float m1 = ((sm[0][2] + sm[1][2]) + (sm[2][2] + sm[3][2])) * (HELPER ? 1.f : 1.f / DM);
            if (HELPER) {
                const float id0 = __uint_as_float(st0.y), id1 = __uint_as_float(st1.y);
                rd0 = SC * id0; rd1 = SC * id1;
                if ((lane & 3) == 0) {
                    sc->r[row] = bf_round((m0 - bf_lo(mm0) * wsum) * id0);
                    sc->r[row + 8] = bf_round((m1 - bf_lo(mm1) * wsum) * id1);
                }
                __syncwarp();
                if (job == 3 && lane == 0) mbar_arrive(qdone + 40);
            } else {
                mm0 = pack_bf16(m0, m0); mm1 = pack_bf16(m1, m1);
            }
            auto centre = [&](int kt) {
#pragma unroll
                for (int i = 32 * kt; i < 32 * kt + 32; i++) asm volatile("sub.rn.bf16x2 %0, %0, %1;" : "+r"(xa[i]) : "r"((i & 1) ? mm1 : mm0));
            };
            if (!HELPER) {
#pragma unroll
                for (int ks = 0; ks < 8; ks++) squares(xa + 96 + 4 * ks);
            }
            if (!HELPER) centre(0);
            if (wg == 1) bar_arrive(1);
            auto diag = [&](int r, int h) { return (lane & 4) ? sq[r][h + 1] + sq[r + 2][h + 1] : sq[r][h] + sq[r + 2][h]; };
            auto spread = [&](float v) { return __shfl_sync(0xffffffffu, v, (lane & ~3u) | (lane >> 3)) * (1.f / DM); };
            if (!HELPER) { rd0 = diag(0, 0); rd1 = diag(1, 2); }
            PT(10);

            if (HELPER) TR(20 + job * 8 + 1);
            uint32_t qs = 0, qph = HELPER ? job & 1 : 0;
            uint4 gx;
            if (HELPER) {
#pragma unroll
                for (int i = 0; i < 64; i++) acc[i] = 0.f;
            }
            const uint32_t xs16 = ring16 + 3 * T16 + wg * 1024;
            constexpr int SS = HELPER ? 0 : 3;
            auto finish_stats = [&] {
                float v0 = spread(rd0) - m0 * m0, v1 = spread(rd1) - m1 * m1;
                if (__any_sync(0xffffffffu, !(m0 * m0 <= 256.f * v0 && m1 * m1 <= 256.f * v1))) {
                    const uint4* xr = (const uint4*)x + row * (DM / 8) + (lane & 3);
                    v0 = 0.f; v1 = 0.f;
#pragma unroll 1
                    for (int i = 0; i < DM / 32; i++) {
                        const uint4 a = __ldg(xr + 4 * i), b = __ldg(xr + DM + 4 * i);
                        const uint32_t w[8] = {a.x, a.y, a.z, a.w, b.x, b.y, b.z, b.w};
#pragma unroll
                        for (int k = 0; k < 8; k++) {
                            const uint32_t d = bf2_sub(w[k], k < 4 ? mm0 : mm1);
                            float& v = k < 4 ? v0 : v1;
                            v = fmaf(bf_lo(d), bf_lo(d), fmaf(bf_hi(d), bf_hi(d), v));
                        }
                    }
#pragma unroll
                    for (int d = 1; d <= 2; d <<= 1) { v0 += __shfl_xor_sync(0xffffffffu, v0, d); v1 += __shfl_xor_sync(0xffffffffu, v1, d); }
                    v0 *= 1.f / DM; v1 *= 1.f / DM;
                    const float e0 = m0 - bf_lo(mm0), e1 = m1 - bf_lo(mm1);
                    v0 -= e0 * e0; v1 -= e1 * e1;
                }
                const float id0 = inv_den(fmaxf(v0, 0.f)), id1 = inv_den(fmaxf(v1, 0.f));
                rd0 = SC * id0; rd1 = SC * id1;
                if (warp == grp) {
                    mbar_wait(epv, 0);
                    uint32_t tg;
                    asm volatile("ld.shared.u32 %0, [%1];" : "=r"(tg) : "r"(epoch));
                    if ((lane & 3) == 0)
                        asm volatile("st.relaxed.gpu.global.v2.u32 [%0], {%1, %2};\nst.relaxed.gpu.global.v2.u32 [%0 + 64], {%3, %4};"
                                     ::"l"(sc->stat + row), "r"(__byte_perm(mm0, tg, 0x5410)), "f"(id0), "r"(__byte_perm(mm1, tg, 0x5410)), "f"(id1) : "memory");
                }
            };
#pragma unroll 1
            for (int pass = 0;; pass++) {
                const uint32_t hs = my_stash + (pass == 2 ? 0 : pass + 1) * TILE_BYTES;
                uint4* const dst = sc->qoff + ((tile * 4 + pass) * 8 + warp) * 256 + lane;
                auto put = [&](int lo) {
#pragma unroll
                    for (int i = lo; i < lo + 4; i++) {
                        const uint4 v = make_uint4(pack_bf16(acc[8 * i] * rd0, acc[8 * i + 1] * rd0), pack_bf16(acc[8 * i + 2] * rd1, acc[8 * i + 3] * rd1),
                                                   pack_bf16(acc[8 * i + 4] * rd0, acc[8 * i + 5] * rd0), pack_bf16(acc[8 * i + 6] * rd1, acc[8 * i + 7] * rd1));
                        if (HELPER) dst[i * 32] = v;
                        else sts128(hs + i * 512, v.x, v.y, v.z, v.w);
                        if (i == 3) sched_fence(zero);
                    }
                };
                auto gate_load = [&](int j) {
                    const uint32_t* src = (const uint32_t*)x + (qt * 128 + warp * 16 + (lane >> 2)) * (DM / 2) + (lane & 3) +
                                          (j < 4 ? grp * 32 + j * 8 : 256 + grp * 8);
                    asm volatile("ld.global.nc.u32 %0, [%4];\nld.global.nc.u32 %1, [%4 + %5];\n"
                                 "ld.global.nc.u32 %2, [%4 + 16];\nld.global.nc.u32 %3, [%4 + %5 + 16];"
                                 : "=r"(gx.x), "=r"(gx.y), "=r"(gx.z), "=r"(gx.w) : "l"(src), "n"(8 * DM * 2));
                };
                auto gate_store = [&](int j) {
                    const float id0 = rd0 * (1.f / SC), id1 = rd1 * (1.f / SC);
                    uint4* g = sc->gate + (blockIdx.x * 5 + j) * 512 + threadIdx.x;
                    g[0] = gx;
                    g[256] = make_uint4(silu2_ln(normalise(gx.x, mm0, id0)), silu2_ln(normalise(gx.y, mm1, id1)),
                                        silu2_ln(normalise(gx.z, mm0, id0)), silu2_ln(normalise(gx.w, mm1, id1)));
                };
                auto advance = [&] {
                    const uint32_t r = rel ? rel + 8 * qs : 0;
                    if (++qs == 2) qph ^= 1;
                    if (qs == 3) qs = 0;
                    return r;
                };
                if (!HELPER && pass == 1) {
#pragma unroll
                    for (int turn = 0; turn < 3; turn++) {
                        if (turn) mbar_wait(full + 8 * qs, qph);
                        bar_sync(my_bar);
                        const uint32_t tile16 = ring16 + qs * T16;
                        wg_fence();
#pragma unroll
                        for (int ks = 0; ks < (turn == 1 ? 8 : 16); ks++) {
                            const uint32_t* a = xa + (turn == 2 ? 64 : turn * 64) + 4 * ks;
                            if (turn == 2 && ks < 8) wgmma_ss64(acc32, desc_kmajor(xs16 - (ks >> 2) * 512, ks), desc_nmajor(tile16, ks), 1);
                            else wgmma_rs64(acc32, a[0], a[1], a[2], a[3], desc_nmajor(tile16, ks), turn || ks);
                        }
                        wg_commit();
                        bar_arrive(other_bar);
                        const uint32_t rl = advance();
                        if (turn == 2) mbar_wait(full + 8 * qs, qph);
                        wg_wait<0>();
                        TA(5 + 2 * turn);
                        release_at<0>(rl);
                    }
                    pin(acc32);
                    put(0);
                    continue;
                }
                uint32_t rl = 0;
#pragma unroll
                for (int kt = 0; kt < 5; kt++) {
                    const bool takes = !HELPER || kt == 0 || kt == 2 || kt == 3, passes = !HELPER || kt == 1 || kt == 2 || kt == 4;
                    if (kt != 0 || pass == 0) mbar_wait(full + 8 * qs, qph);
                    if (takes) bar_sync(my_bar);
                    const uint32_t tile16 = ring16 + qs * T16;
                    wg_fence();
                    if (kt != SS) {
                        mma_tile<1>(acc, xa + (kt < SS ? kt : kt - 1) * 32, tile16, kt != 0);
                    } else {
#pragma unroll
                        for (int ks = 0; ks < 8; ks++) wgmma_ss(acc, desc_kmajor(xs16 - (ks >> 2) * 512, ks), desc_nmajor(tile16, ks), kt || ks);
                        wg_commit();
                    }
                    if (passes && !(HELPER && kt == 4 && pass == 3 && wg == 1)) bar_arrive(other_bar);
                    if (HELPER && pass == 0 && kt < 4) centre(kt);
                    if (!HELPER && pass == 0 && kt < 3) {
#pragma unroll
                        for (int ks = 3 * kt; ks < 3 * kt + 3 && ks < 8; ks++) {
                            const uint32_t ad = ((ring + 3 * TILE_BYTES + lm_off) ^ ((ks & 3) << 5)) + (ks >> 2) * 8192;
                            uint32_t a, b, c, d;
                            ldsm4(ad, a, b, c, d);
                            stsm4(ad, bf2_sub(a, mm0), bf2_sub(b, mm1), bf2_sub(c, mm0), bf2_sub(d, mm1));
                        }
                        if (kt == 2) asm volatile("fence.proxy.async.shared::cta;" ::: "memory");
                    }
                    if (!HELPER && pass == 0 && kt == FINK) finish_stats();
                    if (HELPER && kt == 2 && pass == 3 && job < 3) load_stats(tile + 1);
                    if (!HELPER && pass >= 2 && kt < 4) {
                        if (kt & 1) gate_store((pass - 2) * 2 + (kt >> 1));
                        else gate_load((pass - 2) * 2 + (kt >> 1));
                    }
                    if (!HELPER && pass == G4 && kt == 3) gate_load(4);
                    if (!HELPER && pass == G4 && kt == 4) gate_store(4);
                    const uint32_t rl_prev = rl;
                    rl = advance();
                    if (!passes) continue;
                    if (HELPER && kt != 2) {
                        wg_wait<1>();
                        if (job == 1) TR(120 + pass * 5 + kt - 1);
                        release_at<0>(rl_prev);
                        if (kt == 1 && pass == 3) release_at<24>(rel);
                    }
                    if (kt == 4 && !(HELPER && pass == 3)) mbar_wait(full + 8 * qs, qph);
                    wg_wait<0>();
                    if (!HELPER) TA(pass * 5 + kt);
                    if (HELPER && job == 1) TR(120 + pass * 5 + kt);
                    release_at<0>(rl);
                    if (!HELPER && kt < 3 && pass == 0) centre(kt + 1);
                }
                pin(acc);
                if (!HELPER && pass == 3) break;
                put(0);
                put(4);
                if (HELPER) TR(20 + job * 8 + 2 + pass);
                if (HELPER && pass == 3) {
                    __syncwarp();
                    if (lane == 0) mbar_arrive(qdone + 8 * job);
                    return;
                }
            }
            release_at<24>(rel);
            if (lane == 0) mbar_arrive(gated);
#pragma unroll
            for (int i = 0; i < 32; i++) {
                const float r = (i & 1) ? rd1 : rd0;
                q[i] = pack_bf16(acc[2 * i] * r, acc[2 * i + 1] * r);
            }
        };
        if (helper) {
            const uint32_t ep = sc->epoch[blockIdx.x] + 1;
            if (threadIdx.x < 160) {
                const uint32_t* w32 = (const uint32_t*)wr + (threadIdx.x >> 2) * 8 + (threadIdx.x & 3);
                asm volatile("st.shared.v2.u32 [%0], {%1, %2};" ::"r"(wperm + threadIdx.x * 8), "r"(__ldg(w32)), "r"(__ldg(w32 + 4)) : "memory");
            }
            asm volatile("bar.sync 3, 256;" ::: "memory");
            float ws[4] = {};
#pragma unroll 4
            for (int ks = 0; ks < 40; ks++) {
                uint32_t b0, b1;
                asm volatile("ld.shared.v2.u32 {%0, %1}, [%2];" : "=r"(b0), "=r"(b1) : "r"(wperm + (lane & 3) * 8 + ks * 32));
                hmma(ws, 0x3f803f80u, 0x3f803f80u, 0x3f803f80u, 0x3f803f80u, b0, b1);
            }
            wsum = ws[0];
            ep_tag = ep << 16;
            TR(0);
#pragma unroll 1
            for (int job = 0; job < 4; job++) {
                project(cint<1>(), job);
                TR(1 + job);
            }
            if (elect_one()) mbar_arrive(h1done);
            ffn_role(sc, ring, ffull, fempty, alldone, blockIdx.x - N_MAIN, ep, warp, x);
            return;
        }
        project(cint<0>(), 0);
        TRM(2);
        TG(112);

        float o[64];
        uint32_t p[32];
        float l0, l1;
        constexpr float L_LO = 9.313225746154785e-10f, L_HI = 1.152921504606847e18f;
        float l_hi = L_HI;
        float (&s)[64] = acc;

        auto exp_range = [&](const float (&s)[64], int lo, int hi, float& u0, float& u1) {
            float w0 = 0.f, w1 = 0.f;
#pragma unroll
            for (int i = lo; i < hi; i += 4) {
                const float e0 = ex2(s[i]), e1 = ex2(s[i + 1]), e2 = ex2(s[i + 2]), e3 = ex2(s[i + 3]);
                u0 += e0; u1 += e2;
                if (i == lo) { w0 = e1; w1 = e3; } else { w0 += e1; w1 += e3; }
                p[i / 2] = pack_bf16(e0, e1); p[i / 2 + 1] = pack_bf16(e2, e3);
            }
            u0 += w0; u1 += w1;
        };
        auto unsafe = [&](bool first, float u0, float u1) {
            return (bool)__any_sync(0xffffffffu, !(u0 + u1 <= l_hi) || (first && !(fminf(u0, u1) >= L_LO)));
        };
        auto softmax_true_max = [&](const float (&s)[64], bool first, float b0, float b1, float& u0, float& u1) {
            uint32_t t;
            asm volatile("mov.u32 %0, %%tid.x;" : "=r"(t));
            uint4* const st = sc->rare + blockIdx.x * (17 * 256) + t;
            auto ld = [](const uint4* a) {
                uint4 v;
                asm volatile("ld.global.v4.u32 {%0, %1, %2, %3}, [%4];" : "=r"(v.x), "=r"(v.y), "=r"(v.z), "=r"(v.w) : "l"(a) : "memory");
                return v;
            };
#pragma unroll
            for (int i = 0; i < 16; i++)
                asm volatile("st.global.v4.f32 [%0], {%1, %2, %3, %4};" ::"l"(st + i * 256), "f"(s[4 * i]), "f"(s[4 * i + 1]), "f"(s[4 * i + 2]), "f"(s[4 * i + 3]) : "memory");
            float a0 = s[0], a1 = s[2];
#pragma unroll 1
            for (int i = 0; i < 16; i++) {
                const uint4 v = ld(st + i * 256);
                a0 = fmaxf(a0, fmaxf(__uint_as_float(v.x), __uint_as_float(v.y)));
                a1 = fmaxf(a1, fmaxf(__uint_as_float(v.z), __uint_as_float(v.w)));
            }
            float t0 = b0, t1 = b1, sg0 = 0.f, sg1 = 0.f;
            if (l_hi < 0.f) {
                const uint4 v = ld(st + 16 * 256);
                sg0 = __uint_as_float(v.x); sg1 = __uint_as_float(v.y);
            }
#pragma unroll
            for (int d = 1; d <= 2; d <<= 1) {
                a0 = fmaxf(a0, __shfl_xor_sync(0xffffffffu, a0, d)); a1 = fmaxf(a1, __shfl_xor_sync(0xffffffffu, a1, d));
                t0 += __shfl_xor_sync(0xffffffffu, t0, d); t1 += __shfl_xor_sync(0xffffffffu, t1, d);
            }
            if (!first) {
                a0 = fmaxf(a0, l_hi < 0.f ? sg0 : __log2f(t0)); a1 = fmaxf(a1, l_hi < 0.f ? sg1 : __log2f(t1));
            }
            const float al0 = first ? 1.f : ex2(sg0 - a0), al1 = first ? 1.f : ex2(sg1 - a1);
            asm volatile("st.global.v2.f32 [%0], {%1, %2};" ::"l"(st + 16 * 256), "f"(a0), "f"(a1) : "memory");
            l_hi = -1.f;
            u0 = b0 * al0; u1 = b1 * al1;
#pragma unroll 1
            for (int i = 0; i < 16; i++) {
                const uint4 v = ld(st + i * 256);
                const float e0 = ex2(__uint_as_float(v.x) - a0), e1 = ex2(__uint_as_float(v.y) - a0);
                const float e2 = ex2(__uint_as_float(v.z) - a1), e3 = ex2(__uint_as_float(v.w) - a1);
                u0 += e0 + e1; u1 += e2 + e3;
                asm volatile("st.global.v2.u32 [%0], {%1, %2};" ::"l"((uint2*)(st + (i >> 1) * 256) + (i & 1)), "r"(pack_bf16(e0, e1)), "r"(pack_bf16(e2, e3)) : "memory");
            }
#pragma unroll
            for (int i = 0; i < 8; i++) {
                const uint4 v = ld(st + i * 256);
                p[4 * i] = v.x; p[4 * i + 1] = v.y; p[4 * i + 2] = v.z; p[4 * i + 3] = v.w;
            }
            if (&s != &o) {
#pragma unroll
                for (int i = 0; i < 64; i++) o[i] *= (i & 2) ? al1 : al0;
            }
        };
        auto inv_sums = [&](float& i0, float& i1) {
            float a = l0, b = l1;
            a += __shfl_xor_sync(0xffffffffu, a, 1); b += __shfl_xor_sync(0xffffffffu, b, 1);
            a += __shfl_xor_sync(0xffffffffu, a, 2); b += __shfl_xor_sync(0xffffffffu, b, 2);
            i0 = rcp(a); i1 = rcp(b);
        };

        {
            bar_sync(my_bar);
            wg_fence();
            mma_tile<0>(o, q, ring16, 0);
            mbar_wait(full + 8, 0);
            wg_fence();
            mma_tile<0>(s, q, ring16 + T16, 0);
            bar_arrive(other_bar);
            wg_wait<1>();
            TA(20);
            release_at<0>(rel);
            pin(o);
            l0 = 0.f; l1 = 0.f;
            exp_range(o, 0, 64, l0, l1);
            mbar_wait(full + 16, 1);
            wg_wait<0>();
            if (unsafe(true, l0, l1)) softmax_true_max(o, true, 0.f, 0.f, l0, l1);
        }
        uint32_t qsrc = my_stash;
        float il0 = 0.f, il1 = 0.f;
        auto step = [&](auto odd_c, int m) {
            constexpr int ODD = decltype(odd_c)::value;
            constexpr int KS = ODD ? 3 : 1, VS = ODD ? 0 : 2;
            constexpr int SP = ODD ? SPLITO : SPLIT;
            [[maybe_unused]] const int it = 2 * m + ODD;
            const uint32_t ph = m & 1;
            TC(0);
            bar_sync(my_bar);
            TC(1);
            if (ODD || m) {
                wg_fence();
                mma_tile<0>(s, q, ring16 + KS * T16, 0);
            }
            TC(2);
            if (!ODD) {
                if ((m & 7) == 0 && m) {
#pragma unroll
                    for (int i = FSPLIT; i < 8; i++)
                        sts128(qsrc + i * 512,
                               pack_bf16(o[8 * i] * il0, o[8 * i + 1] * il0), pack_bf16(o[8 * i + 2] * il1, o[8 * i + 3] * il1),
                               pack_bf16(o[8 * i + 4] * il0, o[8 * i + 5] * il0), pack_bf16(o[8 * i + 6] * il1, o[8 * i + 7] * il1));
                    qsrc += m == 24 ? -2 * TILE_BYTES : TILE_BYTES;
                }
                wg_fence();
            }
#pragma unroll
            for (int ks = 0; ks < 8; ks++) {
                wgmma_rs<1>(o, p[4 * ks], p[4 * ks + 1], p[4 * ks + 2], p[4 * ks + 3], desc_nmajor(ring16 + VS * T16, ks),
                            (ks == 0 && !ODD) ? ((m & 7) != 0) : 1);
                if (ks == SP / 8 - 1 || ks == 7) wg_commit();
            }
            TC(3);
            bar_arrive(other_bar);
            const bool last = ODD && (m & 7) == 7;
            if (last) {
                inv_sums(il0, il1);
                l0 = 0.f; l1 = 0.f; l_hi = L_HI;
            }
            wg_wait<1>();
            TA(21 + it);
            TC(4);
            release_at<8 * KS>(rel);
            const bool newq = (m & 7) == 7;
            if (!ODD) {
                lds128_if<0>(newq, qsrc, q[0], q[1], q[2], q[3]);
                lds128_if<512>(newq, qsrc, q[4], q[5], q[6], q[7]);
            }
            pin(s);
            float u0 = l0, u1 = l1;
            exp_range(s, 0, SP, u0, u1);
            mbar_wait_hot(full + 8 * (KS ^ 2), ph ^ 1);
            if (!ODD) {
                lds128_if<1024>(newq, qsrc, q[8], q[9], q[10], q[11]);
                lds128_if<1536>(newq, qsrc, q[12], q[13], q[14], q[15]);
                lds128_if<2048>(newq, qsrc, q[16], q[17], q[18], q[19]);
            }
            TC(5);
            wg_wait<0>();
            release_at<8 * VS>(rel);
            pin(o);
            exp_range(s, SP, 64, u0, u1);
            TC(6);
            mbar_wait_hot(full + 8 * (VS ^ 2), ODD ? ph : ph ^ 1);
            if (!ODD) {
                lds128_if<2560>(newq, qsrc, q[20], q[21], q[22], q[23]);
                lds128_if<3072>(newq, qsrc, q[24], q[25], q[26], q[27]);
                lds128_if<3584>(newq, qsrc, q[28], q[29], q[30], q[31]);
            } else if (last) {
#pragma unroll
                for (int i = 0; i < FSPLIT; i++)
                    sts128(qsrc + i * 512,
                           pack_bf16(o[8 * i] * il0, o[8 * i + 1] * il0), pack_bf16(o[8 * i + 2] * il1, o[8 * i + 3] * il1),
                           pack_bf16(o[8 * i + 4] * il0, o[8 * i + 5] * il0), pack_bf16(o[8 * i + 6] * il1, o[8 * i + 7] * il1));
            }
            if (unsafe(last, u0, u1)) softmax_true_max(s, last, l0, l1, u0, u1);
            l0 = u0; l1 = u1;
            TC(7);
            TF(3 + it);
        };
#pragma unroll 1
        for (int m = 0;; m++) {
            step(cint<0>(), m);
            if (m == 31) break;
            step(cint<1>(), m);
        }
        uint32_t ob[64];
        const uint32_t t128 = threadIdx.x & 127;
        uint32_t ep, tag;
        const uint32_t half = 0x8000u;
        auto send = [&](uint4* dst, const float* a) {
            asm volatile("st.relaxed.gpu.global.v4.u32 [%0], {%1, %2, %3, %4};" ::"l"(dst), "r"(lop3<0xD8>(pack_bf16(a[0], a[1]), tag, 0x10000u)),
                         "r"(pack_bf16(a[2], a[3])), "r"(pack_bf16(a[4], a[5])), "r"(pack_bf16(a[6], a[7])) : "memory");
        };
        auto hint = [&](int dst, int job) {
            asm volatile("st.relaxed.gpu.global.u32 [%0], %1;" ::"l"((uint32_t*)(sc->flag + (qt * 8 + dst) * 32 + job) + (warp & 3)), "r"(ep) : "memory");
        };
        float a32[32], own[32];
        auto half_mma = [&](const uint32_t* a, const uint32_t* b, uint32_t t16, int accumulate) {
            wg_fence();
#pragma unroll
            for (int ks = 0; ks < 8; ks++) wgmma_rs64(a32, a[4 * ks], a[4 * ks + 1], a[4 * ks + 2], a[4 * ks + 3], desc_nmajor(t16, ks), ks ? 1 : accumulate);
#pragma unroll
            for (int ks = 0; ks < 8; ks++) wgmma_rs64(a32, b[4 * ks], b[4 * ks + 1], b[4 * ks + 2], b[4 * ks + 3], desc_nmajor(t16, 8 + ks), 1);
            wg_commit();
        };
        auto block_mma = [&](uint32_t sb, uint32_t ph, bool pass_turn) {
            mbar_wait(full + 8 * sb, ph);
            mbar_wait(full + 8 * sb + 8, ph);
            bar_sync(my_bar);
            half_mma(q, ob, ring16 + sb * T16, zero);
            const uint32_t t16 = ring16 + (sb + 1) * T16;
#pragma unroll
            for (int ks = 0; ks < 16; ks++) {
                const uint32_t* a = ks < 8 ? ob + 32 + 4 * ks : p + 4 * (ks - 8);
                wgmma_rs64(a32, a[0], a[1], a[2], a[3], desc_nmajor(t16, ks), 1);
            }
            wg_commit();
            if (pass_turn) bar_arrive(other_bar);
        };
        auto send_strips = [&](int u) {
            const uint32_t t = opaque(t128);
            const int d0 = (grp & 4) ^ (4 * u);
            uint4* dst = sc->part + (((qt * 8 + d0) * 9 + u) * 2 + wg) * 512 + (grp & 3) * 128 + t;
#pragma unroll
            for (int i = 0; i < 4; i++) send(dst + i * 9 * 1024, a32 + 8 * i);
            if ((t & 31) < 4) hint(d0 + (t & 31), u * 8 + (grp & 3) * 2 + wg);
        };
        uint32_t xs[4], gs[4];
        {
            [[maybe_unused]] const int c = 9;
            TS(0);
            auto fetch_o = [&](int lo, int hi) {
#pragma unroll
                for (int i = lo; i < hi; i++)
                    lds128(qsrc + (1 + (i >> 3)) * TILE_BYTES + (i & 7) * 512, ob[4 * i], ob[4 * i + 1], ob[4 * i + 2], ob[4 * i + 3]);
            };
            fetch_o(0, 3);
            bar_sync(my_bar);
            wg_fence();
            mma_tile<1>(o, p, ring16 + 3 * T16, 1);
            sched_fence(zero);
            inv_sums(il0, il1);
            asm volatile("" : "+f"(il0), "+f"(il1));
            sched_fence(zero);
            fetch_o(3, 6);
            wg_fence();
#pragma unroll
            for (int ks = 0; ks < 8; ks++) {
                wgmma_rs64(a32, q[4 * ks], q[4 * ks + 1], q[4 * ks + 2], q[4 * ks + 3], desc_nmajor(ring16, ks), ks);
                if (ks == 3) { wg_commit(); sched_fence(zero); fetch_o(6, 8); wg_fence(); }
            }
            TS(1);
#pragma unroll
            for (int ks = 0; ks < 8; ks++) wgmma_rs64(a32, ob[4 * ks], ob[4 * ks + 1], ob[4 * ks + 2], ob[4 * ks + 3], desc_nmajor(ring16, 8 + ks), 1);
            wg_commit();
            TS(2);
            bar_arrive(other_bar);
            wg_wait<1>();
            release_at<24>(rel);
            pin(o);
#pragma unroll
            for (int i = 0; i < 32; i++) {
                const float r = (i & 1) ? il1 : il0;
                asm volatile("cvt.rn.bf16x2.f32 %0, %1, %2;" : "=r"(p[i]) : "f"(o[2 * i + 1] * r), "f"(o[2 * i] * r));
                if ((i & 7) == 7) fetch_o(8 + (i >> 3) * 2, 10 + (i >> 3) * 2);
            }
            TS(3);
            mbar_wait(full + 8, 0);
            wg_wait<0>();
            release_at<0>(rel);
            __syncwarp();
            if (lane == 0) mbar_arrive(vacant);
            TS(4);
            bar_sync(my_bar);
            half_mma(ob + 32, p, ring16 + T16, 1);
            TS(5);
            bar_arrive(other_bar);
            TRM(66);
            TG(113);
            mbar_wait(routed, 0);
            asm volatile("ld.shared.u32 %0, [%1];" : "=r"(ep) : "r"(epoch));
            tag = ep << 16;
            const uint4* src = sc->gate + (blockIdx.x * 5 + 4) * 512 + threadIdx.x;
            asm volatile("ld.global.cg.v4.u32 {%0, %1, %2, %3}, [%4];" : "=r"(xs[0]), "=r"(xs[1]), "=r"(xs[2]), "=r"(xs[3]) : "l"(src));
            asm volatile("ld.global.cg.v4.u32 {%0, %1, %2, %3}, [%4];" : "=r"(gs[0]), "=r"(gs[1]), "=r"(gs[2]), "=r"(gs[3]) : "l"(src + 256));
            sched_fence(zero);
            wg_wait<0>();
            TS(6);
            release_at<8>(rel);
            pin(a32);
            send_strips(0);
            TS(7);
        }
        uint32_t v[4][4];
        auto stale = [&]() {
            return __any_sync(0xffffffffu, lop3<0xA8>(lop3<0x7E>(v[0][0], v[1][0], tag), lop3<0x7E>(v[2][0], v[3][0], tag), 0x10000u));
        };
        auto recv = [&](int u) {
            mbar_wait(rfull + 16 * u + 8 * wg, 0);
#pragma unroll
            for (int i = 0; i < 4; i++)
                lds128(stash + (u >= 6 ? u - 6 : u) * 16384 + wg * 8192 + i * 2048 + t128 * 16, v[i][0], v[i][1], v[i][2], v[i][3]);
            if (stale()) {
                const uint4* src = sc->part + (((qt * 8 + grp) * 9 + u) * 2 + wg) * 512 + opaque(t128);
                do {
#pragma unroll
                    for (int i = 0; i < 4; i++)
                        asm volatile("ld.relaxed.gpu.global.v4.u32 {%0, %1, %2, %3}, [%4];" : "=r"(v[i][0]), "=r"(v[i][1]), "=r"(v[i][2]), "=r"(v[i][3])
                                     : "l"(src + i * 128) : "memory");
                } while (stale());
            }
            if (u < 3 && lane == 0) mbar_arrive(rdone + (u * 2 + wg) * 8);
        };
        auto accumulate = [&](float* dst, int stride) {
#pragma unroll
            for (int i = 0; i < 4; i++) {
                float* a = dst + stride * i;
                a[0] += bf_lo(v[i][0]);
                a[1] += __uint_as_float(lop3<0xEC>(v[i][0], half, 0xfffe0000u));
#pragma unroll
                for (int k = 1; k < 4; k++) { a[2 * k] += bf_lo(v[i][k]); a[2 * k + 1] += bf_hi(v[i][k]); }
            }
        };
        auto gate = [](uint32_t x2, uint32_t g2, float lo, float hi) {
            uint32_t sv = pack_bf16(lo, hi);
            asm("mul.rn.bf16x2 %0, %0, %1;" : "+r"(sv) : "r"(g2));
            asm("add.rn.bf16x2 %0, %0, %1;" : "+r"(sv) : "r"(x2));
            return sv;
        };
        uint4* const outbox = sc->part + qt * (8 * 9 * 1024) + wg * 512 + t128;
        auto step_o = [&](int f) {
            [[maybe_unused]] const int c = f;
            const uint32_t sb = (f & 1) ? 0 : 2;
            block_mma(sb, (((f + 3) >> 1) ^ f) & 1, true);
            wg_wait<1>();
            const uint32_t rl = rel && f < 7 ? rel + 8 * sb : 0;
            release_at<0>(rl);
            if (f >= 1) recv(f - 1);
            wg_wait<0>();
            TS(0);
            release_at<8>(rl);
            pin(a32);
            if (f == 0) {
                send_strips(1);
            } else {
                const int d = (grp + f) & 7;
#pragma unroll
                for (int i = 0; i < 4; i++) send(outbox + (d * 9 + f + 1) * 1024 + i * 128, a32 + 8 * i);
                if (lane == 0) hint(d, 14 + 2 * f + wg);
            }
            TS(1);
        };
        {
            float st[8] = {};
#pragma unroll 1
            for (int f = 0; f < 3; f++) {
                [[maybe_unused]] const int c = f;
                step_o(f);
                if (f >= 1) accumulate(st, 0);
                TS(2);
            }
            uint32_t w[4];
#pragma unroll
            for (int i = 0; i < 4; i++) w[i] = gate(xs[i], gs[i], st[2 * i], st[2 * i + 1]);
            const bool odd = lane & 1;
            const uint32_t r0 = __shfl_xor_sync(0xffffffffu, odd ? w[0] : w[2], 1), r1 = __shfl_xor_sync(0xffffffffu, odd ? w[1] : w[3], 1);
            uint2* dst = (uint2*)out + (qt * 128 + warp * 16 + (lane >> 2)) * (DM / 4) + 128 + grp * 4 + (lane & 1) * 2 + ((lane >> 1) & 1);
            dst[0] = odd ? make_uint2(r0, w[2]) : make_uint2(w[0], r0);
            dst[2 * DM] = odd ? make_uint2(r1, w[3]) : make_uint2(w[1], r1);
        }
#pragma unroll
        for (int i = 0; i < 32; i++) own[i] = 0.f;
#pragma unroll 1
        for (int f = 3; f < 8; f++) {
            [[maybe_unused]] const int c = f;
            step_o(f);
            accumulate(own, 8);
            TS(2);
        }
        {
            [[maybe_unused]] const int c = 8;
            recv(7);
            accumulate(own, 8);
            TS(7);
            block_mma(2, 1, wg == 0);
            TRM(71);
            TS(0);
            recv(8);
            accumulate(own, 8);
            TS(1);
            wg_wait<1>();
            uint32_t xv[16], gv[16];
            mbar_wait(xgfull, 0);
            if (lane == 0) mbar_arrive(alldone);
#pragma unroll
            for (int j = 0; j < 4; j++) {
                lds128(stash + 3 * 16384 + j * 8192 + threadIdx.x * 16, xv[4 * j], xv[4 * j + 1], xv[4 * j + 2], xv[4 * j + 3]);
                lds128(stash + 3 * 16384 + j * 8192 + 4096 + threadIdx.x * 16, gv[4 * j], gv[4 * j + 1], gv[4 * j + 2], gv[4 * j + 3]);
            }
            TS(2);
            wg_wait<0>();
            pin(a32);
#pragma unroll
            for (int i = 0; i < 32; i++) own[i] += a32[i];
            TS(3);
            const uint32_t tb = ring + warp * 2048;
#pragma unroll
            for (int j = 0; j < 4; j++)
                stsm4(tb + (lane & 15) * 128 + (((2 * j + (lane >> 4)) ^ (lane & 7)) << 4),
                      gate(xv[4 * j], gv[4 * j], own[8 * j], own[8 * j + 1]), gate(xv[4 * j + 1], gv[4 * j + 1], own[8 * j + 2], own[8 * j + 3]),
                      gate(xv[4 * j + 2], gv[4 * j + 2], own[8 * j + 4], own[8 * j + 5]), gate(xv[4 * j + 3], gv[4 * j + 3], own[8 * j + 6], own[8 * j + 7]));
            __syncwarp();
#pragma unroll
            for (int j = 0; j < 4; j++) {
                const uint32_t row = j * 4 + (lane >> 3);
                uint4 v;
                lds128(tb + row * 128 + (((lane & 7) ^ (row & 7)) << 4), v.x, v.y, v.z, v.w);
                ((uint4*)out)[(qt * 128 + warp * 16 + row) * (DM / 8) + grp * 8 + (lane & 7)] = v;
            }
        }
        TRM(73);
        TG(111);
    }
}

typedef CUresult (*EncodeFn)(CUtensorMap*, CUtensorMapDataType, cuuint32_t, void*, const cuuint64_t*, const cuuint64_t*,
                             const cuuint32_t*, const cuuint32_t*, CUtensorMapInterleave, CUtensorMapSwizzle,
                             CUtensorMapL2promotion, CUtensorMapFloatOOBfill);

void make_map(EncodeFn enc, CUtensorMap* tm, const void* ptr, uint64_t cols, uint64_t rows) {
    cuuint64_t gd[2] = {cols, rows};
    cuuint64_t gs[1] = {cols * 2};
    cuuint32_t bd[2] = {64, 128};
    cuuint32_t es[2] = {1, 1};
    enc(tm, CU_TENSOR_MAP_DATA_TYPE_BFLOAT16, 2, const_cast<void*>(ptr), gd, gs, bd, es, CU_TENSOR_MAP_INTERLEAVE_NONE,
        CU_TENSOR_MAP_SWIZZLE_128B, CU_TENSOR_MAP_L2_PROMOTION_L2_256B, CU_TENSOR_MAP_FLOAT_OOB_FILL_NONE);
}

}

extern "C" void kernel_launch(void* const* d_in, const int* in_sizes, int n_in, void* d_out, int out_size) {
    const __nv_bfloat16* x = (const __nv_bfloat16*)d_in[0];
    const __nv_bfloat16* wr = (const __nv_bfloat16*)d_in[6];
    __nv_bfloat16* out = (__nv_bfloat16*)d_out;

    EncodeFn enc = nullptr;
    cudaDriverEntryPointQueryResult qr;
    cudaGetDriverEntryPoint("cuTensorMapEncodeTiled", (void**)&enc, cudaEnableDefault, &qr);
    CUtensorMap tm_x, tm_wq, tm_k, tm_v, tm_wo, tm_g, tm_u, tm_d;
    {
        cuuint64_t gd[3] = {64, SEQ, DM / 64};
        cuuint64_t gs[2] = {DM * 2, 128};
        cuuint32_t bd[3] = {64, 64, 2};
        cuuint32_t es[3] = {1, 1, 1};
        enc(&tm_x, CU_TENSOR_MAP_DATA_TYPE_BFLOAT16, 3, d_in[0], gd, gs, bd, es, CU_TENSOR_MAP_INTERLEAVE_NONE,
            CU_TENSOR_MAP_SWIZZLE_128B, CU_TENSOR_MAP_L2_PROMOTION_L2_256B, CU_TENSOR_MAP_FLOAT_OOB_FILL_NONE);
    }
    make_map(enc, &tm_k, d_in[1], DH, (uint64_t)NH * SEQ);
    make_map(enc, &tm_v, d_in[2], DH, (uint64_t)NH * SEQ);
    make_map(enc, &tm_wq, d_in[3], NH * DH, DM);
    make_map(enc, &tm_wo, d_in[4], DM, NH * DH);
    make_map(enc, &tm_g, d_in[7], FF, DM);
    make_map(enc, &tm_u, d_in[8], FF, DM);
    make_map(enc, &tm_d, d_in[9], DM, FF);
    cudaFuncSetAttribute(fused_attn_kernel, cudaFuncAttributeMaxDynamicSharedMemorySize, SMEM_BYTES);

    Scratch* sc = nullptr;
    cudaGetSymbolAddress((void**)&sc, g_scratch);

    cudaLaunchConfig_t cfg = {};
    cfg.gridDim = dim3(N_MAIN + N_MOE);
    cfg.blockDim = dim3(384);
    cfg.dynamicSmemBytes = SMEM_BYTES;
    cfg.stream = cudaStreamPerThread;
    cudaLaunchAttribute at[1];
    at[0].id = cudaLaunchAttributeClusterDimension;
    at[0].val.clusterDim.x = 2; at[0].val.clusterDim.y = 1; at[0].val.clusterDim.z = 1;
    cfg.attrs = at; cfg.numAttrs = 1;
    cudaLaunchKernelEx(&cfg, fused_attn_kernel, x, wr, out, sc, tm_x, tm_wq, tm_k, tm_v, tm_wo, tm_g, tm_u, tm_d);
}
```
